```python
import torch

def _softmax(x, axis=-1):
    return torch.softmax(x, dim=axis)
def _gelu(x):
    return torch.nn.functional.gelu(x, approximate="tanh")
def _silu(x):
    return torch.nn.functional.silu(x)
def _sigmoid(x):
    return torch.sigmoid(x)
def _layernorm(x, axis=-1, eps=1e-5):
    m = x.mean(dim=axis, keepdim=True)
    v = x.var(dim=axis, keepdim=True, unbiased=False)
    return (x - m) / torch.sqrt(v + eps)
def _scatter_add(tgt, idx, src, axis=0):
    return tgt.clone().index_add_(axis, idx, src)
def _segment_sum(src, seg, n):
    out = torch.zeros((n,) + src.shape[1:], dtype=src.dtype)
    return out.index_add_(0, seg, src)
def _pad(x, pw):
    flat = tuple(v for pair in reversed(pw) for v in pair)
    return torch.nn.functional.pad(x, flat)

kernel_name = 'standalone__attention_interact_autoint__recsys'

def setup_inputs():

    _w = (lambda a: (lambda t: t.to(torch.bfloat16) if t.is_floating_point() else t)(torch.as_tensor(a)))
    B, F = 4096, 100
    D = max(2, (128 // 2) * 2)
    H = 2
    Dh = D // H
    return {
        "e": _w((lambda *s: torch.randn(*s, dtype=torch.bfloat16) * 0.05)(B, F, D).to(float)),
        "wq": _w((lambda *s: torch.randn(*s, dtype=torch.bfloat16) * 1.6)(H, D, Dh).to(float)),
        "wk": _w((lambda *s: torch.randn(*s, dtype=torch.bfloat16) * 1.6)(H, D, Dh).to(float)),
        "wv": _w((lambda *s: torch.randn(*s, dtype=torch.bfloat16) * 0.05)(H, D, Dh).to(float)),
        "wres": _w((lambda *s: torch.randn(*s, dtype=torch.bfloat16) * 0.05)(D, D).to(float)),
    }

def reference(e, wq, wk, wv, wres):
    H, D, Dh = wq.shape[0], wq.shape[1], wq.shape[2]
    B, F = e.shape[0], e.shape[1]
    q = torch.einsum('bfd,hdk->bhfk', e, wq)
    k = torch.einsum('bfd,hdk->bhfk', e, wk)
    v = torch.einsum('bfd,hdk->bhfk', e, wv)
    scale = float(Dh) ** -0.5
    scores = torch.einsum('bhfk,bhgk->bhfg', q, k) * scale
    attn = _softmax(scores, axis=-1)
    attn = (lambda x, dt: x.to(dt))(attn, v.dtype)
    ctx = torch.einsum('bhfg,bhgk->bhfk', attn, v)
    ctx = (lambda x, *d: x.permute(*d))(ctx, 0, 2, 1, 3).reshape(B, F, H * Dh)
    res = torch.einsum('bfd,de->bfe', e, wres)
    out = ctx + res
    mask = (lambda x, dt: x.to(dt))(out > 0, out.dtype)
    return out * mask
```

```cpp
#include <cuda_runtime.h>
#include <cuda_bf16.h>
#include <cuda.h>
#include <stdint.h>
#define NXC 8
#define XIT 0
#define DYN 1
#define PR(i) do {} while (0)
#define PT(i) do {} while (0)
#define PQ(i) do {} while (0)
#define SW 3
#define SKIP 3
#define RJ 11
#define RJP 11
#define DJ 5
#define TT 4
#define TRX 0
#define NSPIN 4096
#define ROT 0
#define SWP 1
#define PP 0
#define FX 15
#define HY 1
#define NOPVB 0
#define NOLD 0
#define ZM 2
#define LOOKA 1
#define RHI 12
#define CVP 0

namespace {

constexpr int kB = 4096, kF = 100, kD = 128;
constexpr int kStages = 4;
constexpr int kElect = 3, kRefill = 2;
constexpr uint32_t kS = 1024;
constexpr int kEHalf = 104 * 128;
constexpr int kEStage = 2 * kEHalf;
constexpr int kETx = 2 * kF * 128;
constexpr int kOOff = 0;
constexpr int kQOff = 13312;
constexpr int kKOff = kQOff + 16384;
constexpr int kPOff = kQOff;
constexpr int kPL = 144;
constexpr int kPGrp = 13 * kPL;
constexpr int kWsOff = kKOff + 13312;
constexpr int kWGRegion = kWsOff + 16384;
constexpr int kWGBase = kStages * kEStage;
constexpr int kBarOff = kWGBase + 2 * kWGRegion;
constexpr int kFlagOff = kBarOff + 256;
constexpr int kClaimOff = kFlagOff + 16;
constexpr int kTagOff = kClaimOff + 16;
constexpr int kTmpOff = kBarOff + 512;
constexpr int kSmemBytes = kTmpOff + 2 * 1536;
static_assert(kWGRegion % 1024 == 0 && kQOff % 1024 == 0 && kKOff % 1024 == 0 && kWsOff % 1024 == 0 && kWGBase % 1024 == 0 &&
              kPOff + 12 * kPGrp + 16 * kPL <= kWsOff && kSmemBytes <= 232448, "smem layout");

__device__ unsigned g_claim[512];
__device__ uint4 g_w[2][21][128];
__device__ unsigned g_state[2], g_seen, g_epoch;

__device__ __forceinline__ uint32_t smem_u32(const void* p) { return (uint32_t)__cvta_generic_to_shared(p); }

__device__ __forceinline__ void wg_fence() { asm volatile("wgmma.fence.sync.aligned;\n" ::: "memory"); }
__device__ __forceinline__ void wg_commit() { asm volatile("wgmma.commit_group.sync.aligned;\n" ::: "memory"); }
template <int N> __device__ __forceinline__ void wg_wait() { asm volatile("wgmma.wait_group.sync.aligned %0;\n" ::"n"(N) : "memory"); }
__device__ __forceinline__ void fence_async() { asm volatile("fence.proxy.async.shared::cta;\n" ::: "memory"); }
__device__ __forceinline__ void bar_sync(int id, int n) { asm volatile("bar.sync %0, %1;\n" ::"r"(id), "r"(n) : "memory"); }
__device__ __forceinline__ void bar_arrive(int id, int n) { asm volatile("bar.arrive %0, %1;\n" ::"r"(id), "r"(n) : "memory"); }

#define ACC_REGS "{%0,%1,%2,%3,%4,%5,%6,%7,%8,%9,%10,%11,%12,%13,%14,%15,%16,%17,%18,%19,%20,%21,%22,%23,%24,%25," \
                 "%26,%27,%28,%29,%30,%31,%32,%33,%34,%35,%36,%37,%38,%39,%40,%41,%42,%43,%44,%45,%46,%47,%48,%49,%50,%51}"
#define ACC_OPS(c, d)                                                                                        \
  c(d[0]), c(d[1]), c(d[2]), c(d[3]), c(d[4]), c(d[5]), c(d[6]), c(d[7]), c(d[8]), c(d[9]), c(d[10]),        \
  c(d[11]), c(d[12]), c(d[13]), c(d[14]), c(d[15]), c(d[16]), c(d[17]), c(d[18]), c(d[19]), c(d[20]),        \
  c(d[21]), c(d[22]), c(d[23]), c(d[24]), c(d[25]), c(d[26]), c(d[27]), c(d[28]), c(d[29]), c(d[30]),        \
  c(d[31]), c(d[32]), c(d[33]), c(d[34]), c(d[35]), c(d[36]), c(d[37]), c(d[38]), c(d[39]), c(d[40]),        \
  c(d[41]), c(d[42]), c(d[43]), c(d[44]), c(d[45]), c(d[46]), c(d[47]), c(d[48]), c(d[49]), c(d[50]), c(d[51])

__device__ __forceinline__ void fence_acc(float (&d)[52]) {
  asm volatile("" : ACC_OPS("+f", d)::"memory");
}

template <bool ACC>
__device__ __forceinline__ void mma_rs(float (&d)[52], uint32_t a0, uint32_t a1, uint32_t a2, uint32_t a3, uint64_t db) {
  if constexpr (ACC) {
    asm volatile("wgmma.mma_async.sync.aligned.m64n104k16.f32.bf16.bf16 " ACC_REGS
                 ", {%52,%53,%54,%55}, %56, 1, 1, 1, 0;\n"
                 : ACC_OPS("+f", d)
                 : "r"(a0), "r"(a1), "r"(a2), "r"(a3), "l"(db));
  } else {
    asm volatile("wgmma.mma_async.sync.aligned.m64n104k16.f32.bf16.bf16 " ACC_REGS
                 ", {%52,%53,%54,%55}, %56, 0, 1, 1, 0;\n"
                 : ACC_OPS("=f", d)
                 : "r"(a0), "r"(a1), "r"(a2), "r"(a3), "l"(db));
  }
}
template <bool ACC>
__device__ __forceinline__ void mma_ss(float (&d)[52], uint64_t da, uint64_t db) {
  if constexpr (ACC) {
    asm volatile("wgmma.mma_async.sync.aligned.m64n104k16.f32.bf16.bf16 " ACC_REGS ", %52, %53, 1, 1, 1, 0, 0;\n"
                 : ACC_OPS("+f", d)
                 : "l"(da), "l"(db));
  } else {
    asm volatile("wgmma.mma_async.sync.aligned.m64n104k16.f32.bf16.bf16 " ACC_REGS ", %52, %53, 0, 1, 1, 0, 0;\n"
                 : ACC_OPS("=f", d)
                 : "l"(da), "l"(db));
  }
}

__device__ __forceinline__ void mma_ss_tied(float (&d)[52], uint64_t da, uint64_t db) {
  asm volatile("wgmma.mma_async.sync.aligned.m64n104k16.f32.bf16.bf16 " ACC_REGS ", %52, %53, 0, 1, 1, 0, 0;\n"
               : ACC_OPS("+f", d)
               : "l"(da), "l"(db));
}
template <bool ACC>
__device__ __forceinline__ void mma_ss_ta(float (&d)[52], uint64_t da, uint64_t db) {
  if constexpr (ACC) {
    asm volatile("wgmma.mma_async.sync.aligned.m64n104k16.f32.bf16.bf16 " ACC_REGS ", %52, %53, 1, 1, 1, 1, 0;\n"
                 : ACC_OPS("+f", d)
                 : "l"(da), "l"(db));
  } else {
    asm volatile("wgmma.mma_async.sync.aligned.m64n104k16.f32.bf16.bf16 " ACC_REGS ", %52, %53, 0, 1, 1, 1, 0;\n"
                 : ACC_OPS("=f", d)
                 : "l"(da), "l"(db));
  }
}

__device__ __forceinline__ void mma_ss_ta_half(float (&d)[52], uint64_t da, uint64_t db) {
  asm volatile("wgmma.mma_async.sync.aligned.m64n104k16.f32.bf16.bf16 " ACC_REGS ", %52, %53, 0, 1, 1, 1, 0;\n"
               : "+f"(d[0]), "+f"(d[1]), "=f"(d[2]), "=f"(d[3]), "+f"(d[4]), "+f"(d[5]), "=f"(d[6]), "=f"(d[7]), "+f"(d[8]), "+f"(d[9]), "=f"(d[10]), "=f"(d[11]), "+f"(d[12]), "+f"(d[13]), "=f"(d[14]), "=f"(d[15]), "+f"(d[16]), "+f"(d[17]), "=f"(d[18]), "=f"(d[19]), "+f"(d[20]), "+f"(d[21]), "=f"(d[22]), "=f"(d[23]), "+f"(d[24]), "+f"(d[25]), "=f"(d[26]), "=f"(d[27]), "+f"(d[28]), "+f"(d[29]), "=f"(d[30]), "=f"(d[31]), "+f"(d[32]), "+f"(d[33]), "=f"(d[34]), "=f"(d[35]), "+f"(d[36]), "+f"(d[37]), "=f"(d[38]), "=f"(d[39]), "+f"(d[40]), "+f"(d[41]), "=f"(d[42]), "=f"(d[43]), "+f"(d[44]), "+f"(d[45]), "=f"(d[46]), "=f"(d[47]), "+f"(d[48]), "+f"(d[49]), "=f"(d[50]), "=f"(d[51])
               : "l"(da), "l"(db));
}
__device__ __forceinline__ uint64_t desc_sw128(uint32_t saddr) {
  return (uint64_t)((saddr & 0x3FFFF) >> 4) | ((uint64_t)1 << 16) | ((uint64_t)(1024 >> 4) << 32) | ((uint64_t)1 << 62);
}
__device__ __forceinline__ uint64_t desc_p(uint32_t saddr) {
  return (uint64_t)((saddr & 0x3FFFF) >> 4) | ((uint64_t)(kPL >> 4) << 16) | ((uint64_t)(kPGrp >> 4) << 32);
}

__device__ __forceinline__ uint32_t pack_bf16(float lo, float hi) {
  uint32_t r;
  asm("cvt.rn.bf16x2.f32 %0, %1, %2;\n" : "=r"(r) : "f"(hi), "f"(lo));
  return r;
}
__device__ __forceinline__ uint32_t pack_bf16_relu(float lo, float hi) {
  uint32_t r;
  asm("cvt.rn.relu.bf16x2.f32 %0, %1, %2;\n" : "=r"(r) : "f"(hi), "f"(lo));
  return r;
}
__device__ __forceinline__ float ex2(float x) {
  float y;
  asm("ex2.approx.ftz.f32 %0, %1;\n" : "=f"(y) : "f"(x));
  return y;
}
__device__ __forceinline__ float rcp(float x) {
  float y;
  asm("rcp.approx.ftz.f32 %0, %1;\n" : "=f"(y) : "f"(x));
  return y;
}
__device__ __forceinline__ void stsm_x4(uint32_t addr, uint32_t r0, uint32_t r1, uint32_t r2, uint32_t r3) {
  asm volatile("stmatrix.sync.aligned.m8n8.x4.shared.b16 [%0], {%1,%2,%3,%4};\n" ::"r"(addr), "r"(r0), "r"(r1), "r"(r2), "r"(r3) : "memory");
}
__device__ __forceinline__ void stsm_x2(uint32_t addr, uint32_t r0, uint32_t r1) {
  asm volatile("stmatrix.sync.aligned.m8n8.x2.shared.b16 [%0], {%1,%2};\n" ::"r"(addr), "r"(r0), "r"(r1) : "memory");
}
__device__ __forceinline__ void stsm_x1(uint32_t addr, uint32_t r0) {
  asm volatile("stmatrix.sync.aligned.m8n8.x1.shared.b16 [%0], {%1};\n" ::"r"(addr), "r"(r0) : "memory");
}
__device__ __forceinline__ void stsm_x4_t(uint32_t addr, uint32_t r0, uint32_t r1, uint32_t r2, uint32_t r3) {
  asm volatile("stmatrix.sync.aligned.m8n8.x4.trans.shared.b16 [%0], {%1,%2,%3,%4};\n" ::"r"(addr), "r"(r0), "r"(r1), "r"(r2), "r"(r3) : "memory");
}
__device__ __forceinline__ void stsm_x2_t(uint32_t addr, uint32_t r0, uint32_t r1) {
  asm volatile("stmatrix.sync.aligned.m8n8.x2.trans.shared.b16 [%0], {%1,%2};\n" ::"r"(addr), "r"(r0), "r"(r1) : "memory");
}
__device__ __forceinline__ void ldsm_x4_t(uint32_t addr, uint32_t& r0, uint32_t& r1, uint32_t& r2, uint32_t& r3) {
  asm volatile("ldmatrix.sync.aligned.m8n8.x4.trans.shared.b16 {%0,%1,%2,%3}, [%4];\n" : "=r"(r0), "=r"(r1), "=r"(r2), "=r"(r3) : "r"(addr) : "memory");
}
__device__ __forceinline__ int lds16(uint32_t addr) {
  uint16_t v;
  asm volatile("ld.shared.u16 %0, [%1];\n" : "=h"(v) : "r"(addr) : "memory");
  return v;
}
__device__ __forceinline__ int lds(uint32_t addr) {
  int v;
  asm volatile("ld.shared.u32 %0, [%1];\n" : "=r"(v) : "r"(addr) : "memory");
  return v;
}
__device__ __forceinline__ int4 lds4(uint32_t addr) {
  int4 v;
  asm volatile("ld.shared.v4.u32 {%0,%1,%2,%3}, [%4];\n" : "=r"(v.x), "=r"(v.y), "=r"(v.z), "=r"(v.w) : "r"(addr) : "memory");
  return v;
}
__device__ __forceinline__ void sts(uint32_t addr, int v) { asm volatile("st.shared.u32 [%0], %1;\n" ::"r"(addr), "r"(v) : "memory"); }
__device__ __forceinline__ void sts4(uint32_t addr, int x, int y, int z, int w) {
  asm volatile("st.shared.v4.u32 [%0], {%1,%2,%3,%4};\n" ::"r"(addr), "r"(x), "r"(y), "r"(z), "r"(w) : "memory");
}
__device__ __forceinline__ void mbar_init(uint32_t bar, int count) {
  asm volatile("mbarrier.init.shared::cta.b64 [%0], %1;\n" ::"r"(bar), "r"(count) : "memory");
}
__device__ __forceinline__ void mbar_expect_tx(uint32_t bar, int bytes) {
  asm volatile("mbarrier.arrive.expect_tx.shared::cta.b64 _, [%0], %1;\n" ::"r"(bar), "r"(bytes) : "memory");
}
__device__ __forceinline__ void mbar_wait(uint32_t bar, uint32_t parity) {
  asm volatile(
      "{\n.reg .pred p;\n"
      "WAIT_%=:\n"
      "mbarrier.try_wait.parity.shared::cta.b64 p, [%0], %1;\n"
      "@p bra DONE_%=;\n"
      "bra WAIT_%=;\n"
      "DONE_%=:\n}\n" ::"r"(bar), "r"(parity) : "memory");
}
__device__ __forceinline__ void tma_load_2d(uint32_t dst, const CUtensorMap* tm, int c0, int c1, uint32_t bar) {
  asm volatile("cp.async.bulk.tensor.2d.shared::cluster.global.mbarrier::complete_tx::bytes [%0], [%1, {%3, %4}], [%2];\n" ::"r"(dst),
               "l"(tm), "r"(bar), "r"(c0), "r"(c1) : "memory");
}
__device__ __forceinline__ void tma_store_2d(const CUtensorMap* tm, uint32_t src, int c0, int c1) {
  asm volatile("cp.async.bulk.tensor.2d.global.shared::cta.bulk_group [%0, {%2, %3}], [%1];\n" ::"l"(tm), "r"(src), "r"(c0), "r"(c1) : "memory");
}

__device__ __forceinline__ void mma_rs_tied(float (&d)[52], uint32_t a0, uint32_t a1, uint32_t a2, uint32_t a3, uint64_t db) {
  asm volatile("wgmma.mma_async.sync.aligned.m64n104k16.f32.bf16.bf16 " ACC_REGS ", {%52,%53,%54,%55}, %56, 0, 1, 1, 0;\n"
               : ACC_OPS("+f", d)
               : "r"(a0), "r"(a1), "r"(a2), "r"(a3), "l"(db));
}
template <bool TIED = false>
__device__ __forceinline__ void proj(float (&acc)[52], const uint32_t (&w)[32], uint64_t de) {
#pragma unroll
  for (int s = 0; s < 8; s++) {
    uint64_t db = de + (uint64_t)(((s >> 2) * kEHalf + (s & 3) * 32) >> 4);
    if (s == 0) { if (TIED) mma_rs_tied(acc, w[0], w[1], w[2], w[3], db); else mma_rs<false>(acc, w[0], w[1], w[2], w[3], db); }
    else mma_rs<true>(acc, w[4 * s], w[4 * s + 1], w[4 * s + 2], w[4 * s + 3], db);
  }
}
__device__ __forceinline__ void proj_v(float (&acc)[52], const uint32_t (&w)[32], uint64_t de) {
#pragma unroll
  for (int s = 3; s < 8; s++) {
    uint64_t db = de + (uint64_t)(((s >> 2) * kEHalf + (s & 3) * 32) >> 4);
    mma_rs<true>(acc, w[4 * s], w[4 * s + 1], w[4 * s + 2], w[4 * s + 3], db);
  }
}
__device__ __forceinline__ void mma_rs_half(float (&d)[52], uint32_t a0, uint32_t a1, uint32_t a2, uint32_t a3, uint64_t db) {
  asm volatile("wgmma.mma_async.sync.aligned.m64n104k16.f32.bf16.bf16 " ACC_REGS ", {%52,%53,%54,%55}, %56, 0, 1, 1, 0;\n"
               : "+f"(d[0]), "+f"(d[1]), "=f"(d[2]), "=f"(d[3]), "+f"(d[4]), "+f"(d[5]), "=f"(d[6]), "=f"(d[7]), "+f"(d[8]), "+f"(d[9]), "=f"(d[10]), "=f"(d[11]), "+f"(d[12]), "+f"(d[13]), "=f"(d[14]), "=f"(d[15]), "+f"(d[16]), "+f"(d[17]), "=f"(d[18]), "=f"(d[19]), "+f"(d[20]), "+f"(d[21]), "=f"(d[22]), "=f"(d[23]), "+f"(d[24]), "+f"(d[25]), "=f"(d[26]), "=f"(d[27]), "+f"(d[28]), "+f"(d[29]), "=f"(d[30]), "=f"(d[31]), "+f"(d[32]), "+f"(d[33]), "=f"(d[34]), "=f"(d[35]), "+f"(d[36]), "+f"(d[37]), "=f"(d[38]), "=f"(d[39]), "+f"(d[40]), "+f"(d[41]), "=f"(d[42]), "=f"(d[43]), "+f"(d[44]), "+f"(d[45]), "=f"(d[46]), "=f"(d[47]), "+f"(d[48]), "+f"(d[49]), "=f"(d[50]), "=f"(d[51])
               : "r"(a0), "r"(a1), "r"(a2), "r"(a3), "l"(db));
}
template <bool HALF>
__device__ __forceinline__ void proj3_rs(float (&acc)[52], const uint32_t (&w)[32], uint64_t de) {
  if (HALF) mma_rs_half(acc, w[0], w[1], w[2], w[3], de); else mma_rs_tied(acc, w[0], w[1], w[2], w[3], de);
  mma_rs<true>(acc, w[4], w[5], w[6], w[7], de + 2);
  mma_rs<true>(acc, w[8], w[9], w[10], w[11], de + 4);
}
__device__ __forceinline__ void proj3_ss(float (&acc)[52], uint64_t de, uint64_t dw) {
  mma_ss_ta_half(acc, dw, de);
  mma_ss_ta<true>(acc, dw + 128, de + 2);
  mma_ss_ta<true>(acc, dw + 256, de + 4);
}
__device__ __forceinline__ void proj5_ss(float (&acc)[52], uint64_t de, uint64_t dw) {
#pragma unroll
  for (int s = 3; s < 8; s++) mma_ss_ta<true>(acc, dw + (uint64_t)(s * 128), de + (uint64_t)(((s >> 2) * kEHalf + (s & 3) * 32) >> 4));
}
template <bool HALF = false>
__device__ __forceinline__ void proj_r(float (&acc)[52], uint64_t de, uint64_t dw) {
#pragma unroll
  for (int s = 0; s < 8; s++) {
    uint64_t db = de + (uint64_t)(((s >> 2) * kEHalf + (s & 3) * 32) >> 4);
    if (s == 0) { if (HALF) mma_ss_ta_half(acc, dw, db); else mma_ss_ta<false>(acc, dw, db); }
    else mma_ss_ta<true>(acc, dw + (uint64_t)(s * 128), db);
  }
}

template <bool RELU>
__device__ __forceinline__ void store_t(const float (&a)[52], uint32_t addr) {
  auto pk = [&](int i) { return RELU ? pack_bf16_relu(a[i], a[i + 1]) : pack_bf16(a[i], a[i + 1]); };
#pragma unroll
  for (int j = 0; j < 12; j += 2) stsm_x4_t(addr + j * 1024, pk(4 * j), pk(4 * j + 2), pk(4 * j + 4), pk(4 * j + 6));
  stsm_x2_t(addr + 12 * 1024, pk(48), pk(50));
}
__device__ __forceinline__ void store_q_t(const float (&a)[52], uint32_t addr, uint32_t addr_hi, uint32_t addr_last, int src) {
  auto pk = [&](int i) { return pack_bf16(a[i], a[i + 1]); };
#pragma unroll
  for (int w = 0; w < 4; w++) {
    stsm_x4_t(addr + kQOff + 2 * w * 1024, pk(12 * w), pk(12 * w + 2), pk(12 * w + 4), pk(12 * w + 6));
    if (w & 1) stsm_x4_t(addr_hi + kQOff + (6 + 2 * w) * 1024, pk(12 * w - 4), pk(12 * w - 2), pk(12 * w + 8), pk(12 * w + 10));
  }
  const uint32_t r0 = __shfl_sync(0xffffffffu, pk(48), src), r1 = __shfl_sync(0xffffffffu, pk(50), src);
  stsm_x4_t(addr_last, r0, r1, r0, r1);
  stsm_x4_t(addr_last ^ 0x240, r0, r1, r0, r1);
}

constexpr float kC = 0.125f * 1.4426950408889634f;

__device__ __forceinline__ float quad_sum(float t) {
  t += __shfl_xor_sync(0xffffffffu, t, 1);
  t += __shfl_xor_sync(0xffffffffu, t, 2);
  return t;
}
#define PIN(x) asm volatile("" : "+f"(x)::"memory")
struct Q3 { float t, s1, s2, s3; };
__device__ __forceinline__ Q3 q3_start(float t, int m) {
  Q3 q;
  q.t = t;
  q.s1 = __shfl_xor_sync(0xffffffffu, t, m);
  q.s2 = __shfl_xor_sync(0xffffffffu, t, 2 * m);
  q.s3 = __shfl_xor_sync(0xffffffffu, t, 3 * m);
  return q;
}
__device__ __forceinline__ float q3_end(const Q3& q) { return (q.t + q.s1) + (q.s2 + q.s3); }
template <bool TIGHT> __device__ __forceinline__ bool out_of_range(float t) {
  return TIGHT ? !(t >= 0x1p-7f && t <= (float)(1 << RHI)) : !(t >= 0x1p-30f && t <= 0x1p30f);
}

template <int O> __device__ __forceinline__ void set_exp(float (&s)[52], int j, float& t, bool tail_invalid) {
  s[4 * j + O] = ex2(s[4 * j + O]);
  s[4 * j + O + 1] = ex2(s[4 * j + O + 1]);
  if (j == 0) t = s[O] + s[O + 1];
  else if (j < 12 || !tail_invalid) { t += s[4 * j + O]; t += s[4 * j + O + 1]; }
}
template <int O> __device__ __forceinline__ void norm_set(const float (&s)[52], int c, float iv, uint32_t paddr) {
  const int i = 16 * c + O;
  if (c < 3) stsm_x4(paddr + 4 * c * kPL, pack_bf16(s[i] * iv, s[i + 1] * iv), pack_bf16(s[i + 4] * iv, s[i + 5] * iv),
                     pack_bf16(s[i + 8] * iv, s[i + 9] * iv), pack_bf16(s[i + 12] * iv, s[i + 13] * iv));
  else stsm_x1(paddr + 12 * kPL, pack_bf16(s[48 + O] * iv, s[49 + O] * iv));
}
template <int O> __device__ __forceinline__ void set_exact(float (&s)[52], uint32_t paddr, bool tail_invalid) {
  if (tail_invalid) { s[48 + O] = -INFINITY; s[49 + O] = -INFINITY; }
  float m = fmaxf(s[O], s[O + 1]);
#pragma unroll
  for (int j = 1; j < 13; j++) m = fmaxf(m, fmaxf(s[4 * j + O], s[4 * j + O + 1]));
  m = fmaxf(m, __shfl_xor_sync(0xffffffffu, m, 1));
  m = fmaxf(m, __shfl_xor_sync(0xffffffffu, m, 2));
  float t;
#pragma unroll
  for (int j = 0; j < 13; j++) {
    s[4 * j + O] -= m; s[4 * j + O + 1] -= m;
    set_exp<O>(s, j, t, tail_invalid);
  }
  const float iv = rcp(quad_sum(t));
#pragma unroll
  for (int c = 0; c < 4; c++) norm_set<O>(s, c, iv, paddr);
}

__device__ __forceinline__ void sched_barrier() { asm volatile("pmevent 1;\n" ::: "memory"); }

__device__ __forceinline__ void scale_wq(uint32_t (&w)[32]) {
#pragma unroll
  for (int i = 0; i < 32; i++) w[i] = pack_bf16(__uint_as_float(w[i] << 16) * kC, __uint_as_float(w[i] & 0xffff0000u) * kC);
}
__device__ __forceinline__ void issue_s(float (&a)[52], uint64_t dq, uint64_t dk) {
#pragma unroll
  for (int s = 0; s < 4; s++) {
    if (s == 0) mma_ss_tied(a, dq, dk);
    else mma_ss<true>(a, dq + 2 * s, dk + 2 * s);
  }
}
__device__ __forceinline__ void issue_pv(float (&a)[52], const uint32_t (&vf)[26], uint64_t dp, uint32_t z0 = 0, uint32_t z1 = 0) {
#pragma unroll
  for (int s = 0; s < 6; s++) mma_rs<true>(a, vf[4 * s], vf[4 * s + 1], vf[4 * s + 2], vf[4 * s + 3], dp + (kPL / 8) * s);
  mma_rs<true>(a, vf[24], vf[25], z0, z1, (dp + (kPL / 8) * 6) & ~((uint64_t)0x3FFF << 16));
}

__device__ __forceinline__ void exact_redo(const CUtensorMap* tm_e, const CUtensorMap* tm_o, const CUtensorMap* tm_q,
                                        const CUtensorMap* tm_k, const CUtensorMap* tm_v, int n_iter, int n_tiles, int n_base, int n_extra,
                                           uint32_t flags) {
  constexpr uint32_t sbase = kS;
  auto zero = [&]() {
    uint32_t z;
    asm volatile("ld.volatile.shared.u32 %0, [%1];\n" : "=r"(z) : "r"(sbase + kF * 128) : "memory");
    return z;
  };
  const int tid = threadIdx.x + zero(), wg = tid >> 7, warp = (tid >> 5) & 3, lane = tid & 31;
  const int grid = gridDim.x, cta = blockIdx.x, head = wg ^ (cta & 1);
  const uint32_t wgb = sbase + kWGBase + wg * kWGRegion;
  const uint32_t bar_w = sbase + kBarOff + 64 + 32 * wg, bar_e = sbase + kBarOff + 128 + 8 * wg;
  const bool elected = warp == kElect && lane == 0;
  const bool tail_invalid = (lane & 2) != 0;
  const uint32_t t_addr = wgb + ((lane >> 4) * 8 + (lane & 7)) * 128 + (((2 * warp + ((lane >> 3) & 1)) ^ (lane & 7)) << 4);
  const uint32_t q12_k = (2 * (lane >> 4) + ((lane >> 2) & 1) + 2 * (lane & 3)) & 7;
  uint32_t q12_addr = wgb + kQOff + (9 + 2 * (lane & 3)) * 1024 + q12_k * 128 + (((2 * warp + ((lane >> 3) & 1)) ^ q12_k) << 4);
  const uint32_t p8_addr = wgb + kPOff + lane * 16 + (kPL - 128) / 8 * (lane & 24);
  auto e_desc = [&](int st) { return desc_sw128(sbase + (st + wg + zero()) * kEStage); };
  auto g_addr = [&]() { return wgb + zero(); };

  if (elected) {
    asm volatile("cp.async.bulk.wait_group 0;\n" ::: "memory");
    mbar_expect_tx(bar_w, 3 * 16384);
    tma_load_2d(wgb, tm_q, 0, head * 128, bar_w);
    tma_load_2d(wgb + 16384, tm_k, 0, head * 128, bar_w);
    tma_load_2d(sbase + (2 + wg) * kEStage, tm_v, 0, head * 128, bar_w);
  }
  mbar_wait(bar_w, 1);
  uint32_t wQ[32], wK[32], vf[26];
#pragma unroll
  for (int s = 0; s < 8; s++) {
    ldsm_x4_t(t_addr + s * 2048, wQ[4 * s], wQ[4 * s + 1], wQ[4 * s + 2], wQ[4 * s + 3]);
    ldsm_x4_t(t_addr + 16384 + s * 2048, wK[4 * s], wK[4 * s + 1], wK[4 * s + 2], wK[4 * s + 3]);
  }
  scale_wq(wQ);
  auto publish = [&]() {
    bar_sync(1 + wg, 128);
    fence_async();
  };
  bar_sync(1 + wg, 128);
  float acc1[52], acc2[52];
  uint32_t ph = 0;
  for (int t = 0; t < n_iter; t++) {
    if (!__any_sync(0xffffffffu, (flags >> min(t, 31)) & 1)) continue;
    const int row = t == n_tiles ? lds(sbase + kFlagOff + 12) : (t * grid + (t == 0 ? cta ^ head : t == n_base ? cta - grid + n_extra : cta)) * kF;
    if (elected) {
      mbar_expect_tx(bar_e, kETx);
      tma_load_2d(sbase + wg * kEStage, tm_e, 0, row, bar_e);
      tma_load_2d(sbase + wg * kEStage + kEHalf, tm_e, 64, row, bar_e);
    }
    mbar_wait(bar_e, ph);
    ph ^= 1;
    {
      const uint64_t dE = e_desc(0);
      wg_fence();
      proj(acc2, wQ, dE);
      proj(acc1, wK, dE);
      wg_commit();
    }
    wg_wait<0>();
    fence_acc(acc1);
    fence_acc(acc2);
    store_q_t(acc2, t_addr, t_addr + (lane >> 4) * 1024, q12_addr, lane & 29);
    store_t<false>(acc1, t_addr + kKOff);
    {
      const uint64_t dE = e_desc(0), dWv = e_desc(2);
      wg_fence();
      proj_r(acc2, dE, dWv);
      wg_commit();
    }
    wg_wait<0>();
    fence_acc(acc2);
#pragma unroll
    for (int i = 0; i < 26; i++) vf[i] = pack_bf16(acc2[2 * i], acc2[2 * i + 1]);
    publish();
    {
      const uint32_t g = g_addr();
      const uint64_t dQ = desc_sw128(g + kQOff), dK = desc_sw128(g + kKOff);
      wg_fence();
      issue_s(acc1, dQ, dK);
      issue_s(acc2, dQ + 512, dK);
      wg_commit();
    }
    wg_wait<0>();
    fence_acc(acc1);
    fence_acc(acc2);
    bar_sync(1 + wg, 128);
    set_exact<0>(acc1, p8_addr + 3 * warp * kPGrp, tail_invalid);
    set_exact<2>(acc1, p8_addr + (3 * warp + 1) * kPGrp, tail_invalid);
    set_exact<0>(acc2, p8_addr + (3 * warp + 2) * kPGrp, tail_invalid);
    set_exact<2>(acc2, wgb + kPOff + 12 * kPGrp + (lane >> 3) * kPL + warp * 16, tail_invalid);
    publish();
    {
      const uint32_t g = g_addr();
      const uint64_t dE = e_desc(0), dW = desc_sw128(g + kWsOff), dP = desc_p(g + kPOff);
      wg_fence();
      proj_r(acc1, dE, dW);
      issue_pv(acc1, vf, dP);
      wg_commit();
    }
    wg_wait<0>();
    fence_acc(acc1);
    store_t<true>(acc1, t_addr + kOOff);
    publish();
    if (elected) {
      tma_store_2d(tm_o, wgb + kOOff, head * 64, row);
      asm volatile("cp.async.bulk.commit_group;\n" ::: "memory");
      asm volatile("cp.async.bulk.wait_group 0;\n" ::: "memory");
    }
    bar_sync(1 + wg, 128);
  }
}

#define D32_REGS "{%0,%1,%2,%3,%4,%5,%6,%7,%8,%9,%10,%11,%12,%13,%14,%15,%16,%17,%18,%19,%20,%21,%22,%23,%24,%25,%26,%27,%28,%29,%30,%31}"
#define D32_OPS(c, d)                                                                                        \
  c(d[0]), c(d[1]), c(d[2]), c(d[3]), c(d[4]), c(d[5]), c(d[6]), c(d[7]), c(d[8]), c(d[9]), c(d[10]),        \
  c(d[11]), c(d[12]), c(d[13]), c(d[14]), c(d[15]), c(d[16]), c(d[17]), c(d[18]), c(d[19]), c(d[20]),        \
  c(d[21]), c(d[22]), c(d[23]), c(d[24]), c(d[25]), c(d[26]), c(d[27]), c(d[28]), c(d[29]), c(d[30]), c(d[31])
template <int ACC, int SA, int T>
__device__ __forceinline__ void mma64_ss(float (&d)[32], uint64_t da, uint64_t db) {
  if constexpr (ACC)
    asm volatile("wgmma.mma_async.sync.aligned.m64n64k16.f32.bf16.bf16 " D32_REGS ", %32, %33, 1, %34, 1, %35, %35;\n"
                 : D32_OPS("+f", d) : "l"(da), "l"(db), "n"(SA), "n"(T));
  else
    asm volatile("wgmma.mma_async.sync.aligned.m64n64k16.f32.bf16.bf16 " D32_REGS ", %32, %33, 0, %34, 1, %35, %35;\n"
                 : D32_OPS("=f", d) : "l"(da), "l"(db), "n"(SA), "n"(T));
}
template <int ACC, int T>
__device__ __forceinline__ void mma64_rs(float (&d)[32], const uint32_t* a, uint64_t db) {
  if constexpr (ACC)
    asm volatile("wgmma.mma_async.sync.aligned.m64n64k16.f32.bf16.bf16 " D32_REGS ", {%32,%33,%34,%35}, %36, 1, 1, 1, %37;\n"
                 : D32_OPS("+f", d) : "r"(a[0]), "r"(a[1]), "r"(a[2]), "r"(a[3]), "l"(db), "n"(T));
  else
    asm volatile("wgmma.mma_async.sync.aligned.m64n64k16.f32.bf16.bf16 " D32_REGS ", {%32,%33,%34,%35}, %36, 0, 1, 1, %37;\n"
                 : D32_OPS("=f", d) : "r"(a[0]), "r"(a[1]), "r"(a[2]), "r"(a[3]), "l"(db), "n"(T));
}
__device__ __forceinline__ void mma64_done(float (&d)[32]) {
  wg_commit();
  wg_wait<0>();
  asm volatile("" : D32_OPS("+f", d)::"memory");
}
__device__ __forceinline__ float bf_lo(uint32_t x) { return __uint_as_float(x << 16); }
__device__ __forceinline__ float bf_hi(uint32_t x) { return __uint_as_float(x & 0xffff0000u); }
__device__ __forceinline__ void split2(float x, float y, uint32_t& hi, uint32_t& lo) {
  hi = pack_bf16(x, y);
  lo = pack_bf16(x - bf_lo(hi), y - bf_hi(hi));
}
__device__ __forceinline__ float ldsf(uint32_t a) { return __int_as_float(lds(a)); }
__device__ __forceinline__ float2 ldsf2(uint32_t a) {
  float2 v;
  asm volatile("ld.shared.v2.f32 {%0,%1}, [%2];\n" : "=f"(v.x), "=f"(v.y) : "r"(a) : "memory");
  return v;
}
__device__ __forceinline__ float4 ldsf4(uint32_t a) {
  float4 v;
  asm volatile("ld.shared.v4.f32 {%0,%1,%2,%3}, [%4];\n" : "=f"(v.x), "=f"(v.y), "=f"(v.z), "=f"(v.w) : "r"(a) : "memory");
  return v;
}
__device__ __forceinline__ void stsf2(uint32_t a, float x, float y) { asm volatile("st.shared.v2.f32 [%0], {%1,%2};\n" ::"r"(a), "f"(x), "f"(y) : "memory"); }
__device__ __forceinline__ float warp_sum(float t) {
#pragma unroll
  for (int m = 1; m < 32; m *= 2) t += __shfl_xor_sync(0xffffffffu, t, m);
  return t;
}

template <class F>
__device__ __forceinline__ void transform_weights(int zero, int z, int warp, F late_loads) {
  const int t = (threadIdx.x + zero) & 127, lane = t & 31, q = lane & 3, r = 16 * warp + (lane >> 2);
  constexpr uint32_t kWq = kS + kWGBase, kWk = kWq + 16384, kWv = kS + kEStage;
  auto tile_hi = [](int s) { return kS + kWGBase + s * kWGRegion + 32768; };
  auto tile_lo = [](int s) { return kS + (1 + s) * kEStage + 16384; };
  const uint32_t tX = z ? kWv : kWq, tH = tile_hi(z), tL = tile_lo(z);
  const uint32_t big = kS + kWGBase + kWGRegion + z * 16384, gt = kS + z * kEHalf;
  const uint32_t n2 = kS + kTmpOff + z * 1536, buf = kS + 2 * kEStage + z * 1024;
  uint4* dst = &g_w[blockIdx.x][8 * z][t];
  const uint32_t f_addr = kWv + ((lane >> 4) * 8 + (lane & 7)) * 128 + (((2 * warp + ((lane >> 3) & 1)) ^ (lane & 7)) << 4);
  auto store_big = [&](const float (&d)[32]) {
#pragma unroll
    for (int g = 0; g < 8; g++) {
      const uint32_t a = big + r * 256 + ((g ^ (lane >> 2)) << 5) + 8 * q;
      stsf2(a, d[4 * g], d[4 * g + 1]);
      stsf2(a + 2048, d[4 * g + 2], d[4 * g + 3]);
    }
  };
#pragma unroll 1
  for (int i = 0; i < 5; i++) sts4(gt + 16 * t + 2048 * i, 0, 0, 0, 0);
  mbar_wait(kS + kBarOff + 64 + 16 * z, 0);
  PT(1);
  float d[32];
  wg_fence();
#pragma unroll
  for (int s = 0; s < 4; s++) {
    if (s == 0) mma64_ss<0, 1, 0>(d, desc_sw128(tX), desc_sw128(tX));
    else mma64_ss<1, 1, 0>(d, desc_sw128(tX) + 2 * s, desc_sw128(tX) + 2 * s);
  }
  mma64_done(d);
  store_big(d);
  bar_sync(1 + z, 128);
  bool ok = true;
  PT(2);
  {
    const int a = (t >> 4) * 2 + (t & 1), b = (t >> 1) & 7;
    float m[3][6], rs[3], cs[6];
    auto diag = [&](int i) { return rsqrtf(ldsf(big + i * 256 + ((4 * i) ^ ((i & 7) << 5)))); };
#pragma unroll
    for (int i = 0; i < 3; i++) {
      rs[i] = diag(a + 16 * i); cs[2 * i] = diag(2 * b + 16 * i); cs[2 * i + 1] = diag(2 * b + 16 * i + 1);
#pragma unroll
      for (int j = 0; j < 3; j++) {
        const float2 v = ldsf2(big + (a + 16 * i) * 256 + ((8 * b + 64 * j) ^ ((a & 7) << 5)));
        m[i][2 * j] = v.x; m[i][2 * j + 1] = v.y;
      }
    }
#pragma unroll
    for (int i = 0; i < 18; i++) m[i / 6][i % 6] *= rs[i / 6] * cs[i % 6];
    const uint32_t xa = buf + 8 * a, ya = buf + 16 * b;
    const float g0 = a == 2 * b ? 1.f : 0.f, g1 = a == 2 * b + 1 ? 1.f : 0.f;
    auto put = [&](bool own, int o) {
      if (own) {
        m[0][0] -= g0; m[0][1] -= g1;
#pragma unroll
        for (int i = 0; i < 3; i++) stsf2(xa + o + 128 * i, m[i][0], m[i][1]);
        m[0][0] -= g0; m[0][1] -= g1;
      }
    };
#pragma unroll 1
    for (int g = 0; g < 3; g++) {
      put(b == 0, 0);
#pragma unroll 1
      for (int p2 = 0; p2 < 8; p2 += 2) {
#pragma unroll
        for (int u = 0; u < 2; u++) {
          bar_sync(1 + z, 128);
          float4 pv = ldsf4(buf + 16 * p2 + 528 * u), y[3];
          float2 x[3];
#pragma unroll
          for (int i = 0; i < 3; i++) x[i] = ldsf2(xa + 512 * u + 128 * i);
#pragma unroll
          for (int i = 0; i < 3; i++) y[i] = ldsf4(ya + 512 * u + 128 * i);
          pv.x += 1.f; pv.w += 1.f;
          const float id = rcp(pv.x * pv.w - pv.y * pv.y);
          float w[3][2];
#pragma unroll
          for (int i = 0; i < 3; i++) { w[i][0] = (x[i].y * pv.y - x[i].x * pv.w) * id; w[i][1] = (x[i].x * pv.y - x[i].y * pv.x) * id; }
#pragma unroll
          for (int j = 0; j < 3; j++) {
#pragma unroll
            for (int i = 0; i < 3; i++) {
              m[i][2 * j] = fmaf(w[i][0], y[j].x, fmaf(w[i][1], y[j].y, m[i][2 * j]));
              m[i][2 * j + 1] = fmaf(w[i][0], y[j].z, fmaf(w[i][1], y[j].w, m[i][2 * j + 1]));
            }
            if (j == 0) put(b == p2 + u + 1, 512 - 512 * u);
          }
        }
      }
      float o[3][6];
#pragma unroll
      for (int i = 0; i < 18; i++) o[i / 6][i % 6] = m[(i / 6 + 1) % 3][(i % 6 + 2) % 6];
#pragma unroll
      for (int i = 0; i < 18; i++) m[i / 6][i % 6] = o[i / 6][i % 6];
    }
#pragma unroll
    for (int i = 0; i < 3; i++) {
#pragma unroll
      for (int j = 0; j < 3; j++) {
        ok &= fabsf(m[i][2 * j]) <= 32.f;
        ok &= fabsf(m[i][2 * j + 1]) <= 32.f;
        uint32_t hi, lo;
        split2(-rs[i] * cs[2 * j] * m[i][2 * j], -rs[i] * cs[2 * j + 1] * m[i][2 * j + 1], hi, lo);
        const uint32_t o = (a + 16 * i) * 128 + ((4 * b + 32 * j) ^ ((a & 7) << 4));
        sts(tH + o, hi);
        sts(tL + o, lo);
      }
    }
  }
  fence_async();
  bar_sync(1 + z, 128);
  PT(3);
  wg_fence();
#pragma unroll
  for (int s = 0; s < 3; s++) {
    if (s == 0) mma64_ss<0, 1, 1>(d, desc_sw128(tH), desc_sw128(tX));
    else mma64_ss<1, 1, 1>(d, desc_sw128(tH) + 128 * s, desc_sw128(tX) + 128 * s);
    mma64_ss<1, 1, 1>(d, desc_sw128(tL) + 128 * s, desc_sw128(tX) + 128 * s);
  }
  mma64_done(d);
  uint32_t fh[16], fl[16];
  auto split_d = [&]() {
#pragma unroll
    for (int i = 0; i < 16; i++) split2(d[2 * i], d[2 * i + 1], fh[i], fl[i]);
  };
  split_d();
  bar_sync(1 + z, 128);
#pragma unroll
  for (int g = 0; g < 4; g++) {
    const uint32_t c = (16 * warp + (lane & 15)) * 128 + (((2 * g + (lane >> 4)) ^ (lane & 7)) << 4);
    stsm_x4(tH + c, fh[4 * g], fh[4 * g + 1], fh[4 * g + 2], fh[4 * g + 3]);
    stsm_x4(tL + c, fl[4 * g], fl[4 * g + 1], fl[4 * g + 2], fl[4 * g + 3]);
  }
  fence_async();
  bar_sync(1 + z, 128);
  wg_fence();
#pragma unroll
  for (int s = 0; s < 3; s++) {
    if (s == 0) mma64_ss<0, -1, 1>(d, desc_sw128(tX), desc_sw128(tH));
    else mma64_ss<1, -1, 1>(d, desc_sw128(tX) + 128 * s, desc_sw128(tH) + 128 * s);
    mma64_ss<1, -1, 1>(d, desc_sw128(tX) + 128 * s, desc_sw128(tL) + 128 * s);
  }
  mma64_done(d);
  store_big(d);
  bar_sync(1 + z, 128);
  PT(4);
  if (warp == z) {
    const uint32_t da = big + lane * 512 + ((8 * lane) ^ ((lane & 3) << 6)), db = (da ^ 32) + 260;
    float dx = ldsf(da) + 1.f, dy = ldsf(db) + 1.f;
    sts(da, __float_as_int(dx));
    sts(db, __float_as_int(dy));
    float hx[16], hy[16];
#pragma unroll
    for (int i = 0; i < 16; i++) hx[i] = hy[i] = 0.f;
#pragma unroll 1
    for (int c = 0; c < 16; c += 4) {
#pragma unroll
      for (int e = 3; e >= 0; e--) {
        __syncwarp();
        const int key = __reduce_max_sync(0xffffffffu, max((__float_as_int(dx) & ~63) | (2 * lane), (__float_as_int(dy) & ~63) | (2 * lane + 1)));
        const int p = key & 63;
        const float2 row = ldsf2(big + p * 256 + ((8 * lane) ^ ((p & 7) << 5)));
        float k[16];
#pragma unroll
        for (int i = e == 3; i < 4; i++) {
          const float4 v = ldsf4(gt + p * 144 + 48 - 4 * c + 16 * i);
          k[4 * i] = v.x; k[4 * i + 1] = v.y; k[4 * i + 2] = v.z; k[4 * i + 3] = v.w;
        }
        const float is = rsqrtf(__int_as_float(key));
        float ux[2] = {row.x, 0.f}, uy[2] = {row.y, 0.f};
#pragma unroll
        for (int i = e + 1; i < 16; i++) { ux[i & 1] = fmaf(-k[i], hx[i], ux[i & 1]); uy[i & 1] = fmaf(-k[i], hy[i], uy[i & 1]); }
        hx[e] = (ux[0] + ux[1]) * is;
        hy[e] = (uy[0] + uy[1]) * is;
        dx = fmaf(-hx[e], hx[e], dx);
        dy = fmaf(-hy[e], hy[e], dy);
        sts(gt + lane * 288 + 48 - 4 * c + 4 * e, __float_as_int(hx[e]));
        sts(gt + lane * 288 + 192 - 4 * c + 4 * e, __float_as_int(hy[e]));
        ok &= key >= 0x3c000000;
      }
#pragma unroll
      for (int i = 15; i >= 4; i--) { hx[i] = hx[i - 4]; hy[i] = hy[i - 4]; }
    }
    ok &= fmaxf(fabsf(dx), fabsf(dy)) <= 0x1p-10f;
  } else if (warp >= 2) {
#pragma unroll 1
    for (int h = 0; h < 2; h++) {
      const int row = (t & 63) + 64 * h;
      float a = 0.f, b = 0.f;
#pragma unroll 2
      for (int c = 0; c < 8; c++) {
        const int4 v = lds4(tX + row * 128 + ((c ^ (t & 7)) << 4));
        const uint32_t w[4] = {(uint32_t)v.x, (uint32_t)v.y, (uint32_t)v.z, (uint32_t)v.w};
#pragma unroll
        for (int k = 0; k < 4; k++) { a = fmaf(bf_lo(w[k]), bf_lo(w[k]), a); b = fmaf(bf_hi(w[k]), bf_hi(w[k]), b); }
      }
      sts(n2 + 4 * row, __float_as_int(a + b));
    }
    bar_sync(8 + z, 64);
    const float s = warp_sum(ldsf(n2 + 4 * lane) + (lane < 16 ? ldsf(n2 + 128 + 4 * lane) : 0.f)) * (1.f / 48);
    if (t == 64) sts(n2 + 1020, __float_as_int(s));
  }
  bar_sync(1 + z, 128);
  PT(9);
  const float s2 = ldsf(n2 + 1020);
  ok &= (s2 >= 0x1p-60f) & (s2 <= 0x1p60f);
  {
    const float4 gx = ldsf4(gt + lane * 288 + 16 * warp), gy = ldsf4(gt + lane * 288 + 144 + 16 * warp);
    const float vx[4] = {gx.x, gx.y, gx.z, gx.w}, vy[4] = {gy.x, gy.y, gy.z, gy.w};
    float k = rsqrtf(s2);
#pragma unroll 1
    for (int h = 0; h < 2; h++) {
#pragma unroll
      for (int i = 0; i < 4; i++) {
        uint32_t hi, lo;
        const uint32_t o = 6144 + 2048 * h + (4 * warp + i) * 128 + ((4 * lane) ^ (((4 * warp + i) & 7) << 4));
        split2(vx[i] * k, vy[i] * k, hi, lo);
        sts(tH + o, hi);
        sts(tL + o, lo);
      }
      k *= s2;
    }
  }
  fence_async();
  __syncthreads();
  late_loads();
  PT(5);
  {
    const uint32_t tW = z ? kWq : kWv, gH = tile_hi(1 - z) + 8192, gL = tile_lo(1 - z) + 8192;
    auto mm = [&](uint32_t x, uint32_t y, bool first) {
      const uint64_t da = desc_sw128(z ? y : x), db = desc_sw128(z ? x : y);
      if (first) mma64_ss<0, 1, 1>(d, da, db); else mma64_ss<1, 1, 1>(d, da, db);
    };
    wg_fence();
#pragma unroll
    for (int s = 0; s < 3; s++) { mm(tW + 2048 * s, tH + 2048 * s, s == 0); mm(tW + 2048 * s, tL + 2048 * s, false); }
    mm(gH, tH + 6144, false); mm(gH, tL + 6144, false); mm(gL, tH + 6144, false);
    wg_commit();
  }
  const float so = ldsf(kS + kTmpOff + (1 - z) * 1536 + 1020);
  ok &= z | (ldsf(kS + kTmpOff + 4 * t) * so <= 6.f * s2 * ldsf(kS + kTmpOff + 1536 + 4 * t));
  wg_wait<0>();
  asm volatile("" : D32_OPS("+f", d)::"memory");
  float nn = 0.f;
#pragma unroll
  for (int i = 0; i < 32; i++) { nn = fmaf(d[i], d[i], nn); d[i] *= z ? kC : 1.f; }
  split_d();
  mbar_wait(kS + kBarOff + 64 + 8, 0);
  PT(6);
  {
    const uint64_t db = desc_sw128(z ? kWk : kWq);
    float d2[32];
    wg_fence();
#pragma unroll
    for (int s = 0; s < 4; s++) {
      if (s == 0) mma64_rs<0, 0>(d2, fh, db + 512); else mma64_rs<1, 0>(d2, fh + 4 * s, db + 512 + 2 * s);
      mma64_rs<1, 0>(d2, fl + 4 * s, db + 512 + 2 * s);
    }
    wg_commit();
#pragma unroll
    for (int s = 0; s < 4; s++) {
      if (s == 0) mma64_rs<0, 0>(d, fh, db); else mma64_rs<1, 0>(d, fh + 4 * s, db + 2 * s);
      mma64_rs<1, 0>(d, fl + 4 * s, db + 2 * s);
    }
    wg_commit();
    uint32_t v[20];
#pragma unroll
    for (int s = 0; s < 5; s++) ldsm_x4_t(f_addr + (3 + s) * 2048, v[4 * s], v[4 * s + 1], v[4 * s + 2], v[4 * s + 3]);
    auto out = [&](const float* x, int s) {
      uint32_t w[4];
#pragma unroll
      for (int i = 0; i < 4; i++) w[i] = pack_bf16(x[2 * i], x[2 * i + 1]);
      if (s >= 3 || z) dst[s * 128] = make_uint4(w[0], w[1], w[2], w[3]);
      if (s >= 3) {
#pragma unroll
        for (int i = 0; i < 4; i++) asm("sub.rn.bf16x2 %0, %1, %0;\n" : "+r"(w[i]) : "r"(v[4 * s - 12 + i]));
        if (z == 0) dst[(13 + s) * 128] = make_uint4(w[0], w[1], w[2], w[3]);
      }
    };
    wg_wait<1>();
    asm volatile("" : D32_OPS("+f", d2)::"memory");
#pragma unroll
    for (int s = 0; s < 4; s++) out(d2 + 8 * s, 4 + s);
    wg_wait<0>();
    asm volatile("" : D32_OPS("+f", d)::"memory");
#pragma unroll
    for (int s = 0; s < 4; s++) out(d + 8 * s, s);
  }
  ok &= warp_sum(nn) * s2 <= 128.f * so;
  PT(7);
  const int all = __syncthreads_and(ok);
  if (t + z == 0) asm volatile("st.release.gpu.global.u32 [%0], %1;\n" ::"l"(g_state + blockIdx.x), "r"(lds(kS + kTagOff) + (all != 0)) : "memory");
  PT(8);
}

template <int V> struct IC { __device__ constexpr operator int() const { return V; } };
struct WPtrs { const uint8_t* p[4]; };

__global__ void __launch_bounds__(256, 1)
autoint_kernel(const __grid_constant__ CUtensorMap tm_e, const __grid_constant__ CUtensorMap tm_o,
               const __grid_constant__ CUtensorMap tm_q, const __grid_constant__ CUtensorMap tm_k,
               const __grid_constant__ CUtensorMap tm_v, const __grid_constant__ CUtensorMap tm_r,
               const uint8_t* p_e, const __grid_constant__ WPtrs pw,
               const int n_base, const int n_extra, const int n_skip, const int zero, const int n_open) {
  extern __shared__ __align__(1024) uint8_t smem[];
  const int tid = threadIdx.x;
  PR(0);
  if ((tid & 31) == 0 && tid >= 64) asm volatile("prefetch.tensormap [%0];\n" ::"l"((const char*)&tm_e + (tid - 64) * 4) : "memory");
  if (tid < 200) asm volatile("prefetch.global.L2 [%0];\n" ::"l"(p_e + (blockIdx.x & ~1u) * (kF * kD * 2) + tid * 128) : "memory");
  else if (tid < 208) asm volatile("prefetch.global.L2 [%0];\n" ::"l"(pw.p[(blockIdx.x >> 5) & 3] + (blockIdx.x & 31) * 1024 + (tid & 7) * 128) : "memory");
  constexpr uint32_t bar_full = kS + kBarOff;
  constexpr uint32_t bar_w = kS + kBarOff + 64;
  const int grid = gridDim.x, cta = blockIdx.x;
  const int n_tiles = n_base + (cta >= grid - n_extra) - (cta < 2 ? n_skip : 0);
  auto row_of = [&](int t) { return (t * grid + cta - (t == n_base ? grid - n_extra : 0)) * kF; };
  auto load_r = [&](int row, int st, uint32_t bar) {
    mbar_expect_tx(bar, kETx);
    tma_load_2d(kS + st * kEStage, &tm_e, 0, row, bar);
    tma_load_2d(kS + st * kEStage + kEHalf, &tm_e, 64, row, bar);
  };

  auto load_w = [&](int w, int m) {
    const int h = w ^ (cta & 1);
    const uint32_t dst = kS + kWGBase + w * kWGRegion, bar = bar_w + 8 * (4 * w + m);
    mbar_expect_tx(bar, 16384);
    if (m == 0) tma_load_2d(dst, &tm_q, 0, h * 128, bar);
    if (m == 1) tma_load_2d(dst + 16384, &tm_k, 0, h * 128, bar);
    if (m == 2) tma_load_2d(kS + (1 + w) * kEStage, &tm_v, 0, h * 128, bar);
    if (m == 3) tma_load_2d(dst + kWsOff, &tm_r, h * 64, 0, bar);
  };
  if (tid == 0) {
    mbar_init(bar_w + 80, 1);
    mbar_init(bar_w, 1);
    mbar_init(bar_w + 8, 1);
    mbar_init(bar_w + 16, 1);
    asm volatile("fence.mbarrier_init.release.cluster;\n" ::: "memory");
    fence_async();
    load_w(0, 0); load_w(0, 1); load_w(0, 2);
    load_r((cta & ~1) * kF, 3, bar_w + 80);
  } else if (tid == 32) {
    if (smem_u32(smem) != kS) __trap();
    for (int s = 0; s < kStages; s++) mbar_init(bar_full + 8 * s, 1);
    for (int s = 3; s < 10; s++) mbar_init(bar_w + 8 * s, 1);
    asm volatile("fence.mbarrier_init.release.cluster;\n" ::: "memory");
  }
  const int wg_r = __shfl_sync(0xffffffffu, tid >> 7, 0);
  const int warp = __shfl_sync(0xffffffffu, (tid >> 5) & 3, 0);
  const int lane = tid & 31;
  auto st_zero = [&](uint32_t a) { asm volatile("st.shared.v4.u32 [%0], {%1,%1,%1,%1};\n" ::"r"(a), "r"(0) : "memory"); };
  if (tid >= 128) st_zero(kS + (warp + (warp & 2) * 2) * kEHalf + kF * 128 + lane * 16);
  fence_async();
  __syncthreads();
  auto loads2 = [&]() {
    if (tid == 128) {
      load_w(1, 0); load_w(1, 1); load_w(1, 2); load_w(0, 3);
      load_r((cta | 1) * kF, 0, bar_full);
      load_w(1, 3);
    }
  };
  if (cta >= 2) loads2();

  if (tid == 192) sts(kS + kTagOff, 2 * *(volatile unsigned*)&g_epoch + 2);
  if (tid == 160) {
    const int mod = max(n_open, 1), x = (cta >> 1) % mod, y = x - (n_open - 2 * n_skip);
    sts4(kS + kFlagOff, 0, 0, 0, (n_open == 0 ? kB : y < 0 ? n_base * grid + x : (n_base - 1 - (y >> 1)) * grid + (y & 1)) * kF);
    const uint64_t ga = (uint64_t)__cvta_generic_to_global(g_claim + 2 * x + (cta & 1));
    sts4(kS + kClaimOff, (int)ga, (int)(ga >> 32), ((grid >> 1) - 1 - x) / mod, n_open ? n_tiles + 1 : 0);
  }
  if (cta < 2) transform_weights(zero, wg_r, warp, loads2);

  int it = -1;
  bool fast = false;
  uint32_t ln = lane;
  uint32_t wQ[32], wK[32], wV[32], vf[26];
  float acc1[52], acc2[52];
  uint32_t z0 = 0, z1 = 0;
  uint32_t t_addr = kS + kWGBase + (tid >> 7) * kWGRegion + ((lane >> 4) * 8 + (lane & 7)) * 128 + (((2 * warp + ((lane >> 3) & 1)) ^ (lane & 7)) << 4);
  const uint32_t q12_k = (2 * (lane >> 4) + ((lane >> 2) & 1) + 2 * (lane & 3)) & 7;
  uint32_t q12_addr = kS + kWGBase + (tid >> 7) * kWGRegion + kQOff + (9 + 2 * (lane & 3)) * 1024 + q12_k * 128 + (((2 * warp + ((lane >> 3) & 1)) ^ q12_k) << 4);
  asm volatile("xor.b32 %0, %0, %2;\nxor.b32 %1, %1, %2;\n" : "+r"(t_addr), "+r"(q12_addr) : "r"(zero));
  auto tail_inv = [&]() { return (ln & 2) != 0; };
  auto publish = [&](int wg) {
    bar_sync(1 + wg, 128);
    fence_async();
  };
  auto tma_out = [&](int wg, int row) {
    tma_store_2d(&tm_o, kS + kWGBase + wg * kWGRegion + kOOff, (wg ^ (cta & 1)) * 64, row);
    asm volatile("cp.async.bulk.commit_group;\n" ::: "memory");
  };
  auto more = [&](int wg) {
    if (wg == 1) return false;
    if (it + 1 == n_tiles) {
      if (warp == kRefill && ln == 0) {
        const int4 c = lds4(kS + kClaimOff);
        uint32_t k;
        asm volatile("atom.global.inc.u32 %0, [%1], %2;\n" : "=r"(k) : "l"((uint64_t)(uint32_t)c.x | ((uint64_t)(uint32_t)c.y << 32)), "r"(c.z) : "memory");
        if (k == 0) sts(kS + kFlagOff + 8, c.w);
      }
      if (warp == 1 && ln == 0 && atomicInc(&g_seen, grid - 1) == grid - 1) g_epoch = (unsigned)lds(kS + kTagOff) / 2;
      bar_sync(1, 128);
    }
    return it + 1 < lds(kS + kFlagOff + 8);
  };
  auto start = [&](auto wgc) __attribute__((always_inline)) {
    const int wg = wgc;
    auto load_frags = [&](uint32_t (&w)[32], int m) {
      mbar_wait(bar_w + 8 * (4 * wg + m), 0);
      const uint32_t a = m < 2 ? t_addr + m * 16384 : t_addr - (kWGBase - kEStage) - (tid >> 7) * (kWGRegion - kEStage);
#pragma unroll
      for (int s = 0; s < 8; s++) ldsm_x4_t(a + s * 2048, w[4 * s], w[4 * s + 1], w[4 * s + 2], w[4 * s + 3]);
    };
    load_frags(wQ, 0);
    scale_wq(wQ);
    load_frags(wK, 1);
    load_frags(wV, 2);
    bar_sync(1 + wg, 128);
    if (warp < 2) st_zero(kS + (2 + 2 * wg + warp) * kEHalf + kF * 128 + lane * 16);
    if (tid >= 156) {
      const uint8_t* p = p_e + (size_t)(3 * grid + cta) * (kF * kD * 2) + (tid - 156) * 256;
      asm volatile("prefetch.global.L2 [%0];\nprefetch.global.L2 [%0 + 128];\n" ::"l"(p));
    }
    PQ(5);
    if (wg == 1) bar_sync(7, 256);
    if (FX & 8) {
#pragma unroll
      for (int i = 0; i < 52; i++) asm volatile("" : "=f"(acc1[i]));
#pragma unroll
      for (int i = 0; i < 26; i++) asm volatile("" : "=r"(vf[i]));
    }
  };
  auto iter = [&](auto wgc, auto fastc) __attribute__((always_inline)) {
    constexpr bool FAST = fastc;
    const int wg = wgc;
    const uint32_t wgb = kS + kWGBase + wg * kWGRegion;
    const uint64_t dQ = desc_sw128(wgb + kQOff), dK = desc_sw128(wgb + kKOff), dP = desc_p(wgb + kPOff), dW = desc_sw128(wgb + kWsOff);
    auto p8_addr = [&]() { return wgb + kPOff + 3 * warp * kPGrp + ln * 16 + (kPL - 128) / 8 * (ln & 24); };
    auto cvt_v = [&]() {
#pragma unroll
      for (int i = 0; i < 26; i++) vf[i] = pack_bf16(acc2[2 * i], acc2[2 * i + 1]);
      if (ZM == 1) asm volatile("mov.b32 %0, %2;\nmov.b32 %1, %2;\n" : "=r"(z0), "=r"(z1) : "r"(zero));
      if (ZM == 2) asm volatile("and.b32 %0, %2, %3;\nand.b32 %1, %4, %3;\n" : "=r"(z0), "=r"(z1) : "r"(vf[0]), "r"(zero), "r"(vf[1]));
    };
    it++;
    const bool own = !FAST && wg == 0 && it == 0;
    const int stage = own ? 3 : it & 3;
    const uint64_t dE = desc_sw128(kS) + (uint64_t)((stage * kEStage) >> 4);
    if (FAST || NOPVB || it > 0) {
      wg_fence();
      issue_pv(acc1, vf, dP, z0, z1);
      wg_commit();
    }
    mbar_wait(own ? bar_w + 80 : bar_full + 8 * stage, (it >> 2) & 1);
    if (!FAST && it == 0) PQ(6);
    wg_fence();
    proj<(TT >> (FAST ? 3 : 0)) & 1>(acc2, wQ, dE);
    wg_commit();
    wg_wait<1>();
    fence_acc(acc1);
    store_t<true>(acc1, t_addr + kOOff);
    wg_fence();
    proj<(TT >> (FAST ? 4 : 1)) & 1>(acc1, wK, dE);
    wg_commit();
    wg_wait<1>();
    fence_acc(acc2);
    store_q_t(acc2, t_addr, t_addr + (ln & 16) * 64, q12_addr, ln & 29);
    wg_fence();
    if (FAST) proj_v(acc2, wV, dE); else proj<(TT >> 2) & 1>(acc2, wV, dE);
    wg_commit();
    if (!own) bar_arrive(4 - wg, 256);
    wg_wait<1>();
    fence_acc(acc1);
    store_t<false>(acc1, t_addr + kKOff);
    if (FAST) {
      wg_wait<0>();
      fence_acc(acc2);
      cvt_v();
#pragma unroll
      for (int i = 0; i < 26; i++) asm volatile("" : "+r"(vf[i]));
      sched_barrier();
    }
    publish(wg);
    wg_fence();
    issue_s(acc1, dQ + 512, dK);
    wg_commit();
    if (!FAST) {
      wg_wait<1>();
      fence_acc(acc2);
      cvt_v();
      wg_fence();
    }
    issue_s(acc2, dQ, dK);
    wg_commit();
    if (own) bar_arrive(7, 256);
    if (!FAST && it == 0) PQ(7);
    if (warp == kElect && ln == 0) {
      if (!FAST && it == 0) load_r(((1 + wg) * grid + cta) * kF, 1 + wg, bar_full + 8 * (1 + wg));
      else tma_out(wg, !FAST && it == 1 ? ((cta & ~1) | wg) * kF : ((it - 1) * grid + cta) * kF);
    }
    const bool sw = !FAST && it == (cta < 2 ? SWP : SW);
    unsigned state = 0;
    auto poll = [&]() { asm volatile("ld.relaxed.gpu.global.u32 %0, [%1];\n" : "=r"(state) : "l"(g_state + (wg ^ (cta & 1))) : "memory"); };
    wg_wait<1>();
    fence_acc(acc1);
    const float zf = __int_as_float(zero);
    auto q3_dep = [&](const Q3& q, float later) { return ((fmaf(later, zf, q.t) + q.s1) + q.s2) + q.s3; };
    float x[4];
    {
      const bool b0 = ln & 4, b1 = ln & 8, b2 = ln & 16;
#pragma unroll
      for (int h = 0; h < 2; h++) {
        const float* v = acc1 + 2 + h;
        const float x01 = b0 ? v[4] : v[0], x23 = b0 ? v[12] : v[8], x45 = b0 ? v[20] : v[16], x67 = b0 ? v[28] : v[24];
        const float x03 = b1 ? x23 : x01, x47 = b1 ? x67 : x45;
        x[h] = b2 ? x47 : x03;
        const float y01 = b0 ? v[36] : v[32], y23 = b0 ? v[44] : v[40];
        const float y03 = b1 ? y23 : y01;
        x[2 + h] = b2 ? v[48] : y03;
      }
#pragma unroll
      for (int h = 0; h < 4; h++) x[h] = ex2(x[h]);
    }
    float sd = x[0] + x[1];
    if (ln < 18) sd += x[2] + x[3];
    Q3 qd = q3_start(sd, 1);
    float sc;
#pragma unroll
    for (int j = 0; j < 7; j++) set_exp<0>(acc1, j, sc, tail_inv());
    qd = q3_start(q3_dep(qd, acc1[25]), 4);
#pragma unroll
    for (int j = 7; j < 13; j++) set_exp<0>(acc1, j, sc, tail_inv());
    const Q3 qc = q3_start(sc, 1);
    sd = q3_dep(qd, acc1[45]);
    const float sd2 = __shfl_xor_sync(0xffffffffu, sd, 16);
    sched_barrier();
    wg_wait<0>();
    fence_acc(acc2);
    if (sw) {
      PQ(2);
      const unsigned tag = lds(kS + kTagOff);
      int n = 0;
      do { poll(); state -= tag; } while (state > 1 && ++n < NSPIN);
      int all;
      asm volatile("{.reg .pred p, q;\nsetp.eq.u32 q, %1, 1;\nbar.red.and.pred p, %2, 128, q;\nselp.b32 %0, 1, 0, p;}\n" : "=r"(all) : "r"(state), "r"(1 + wg) : "memory");
      fast = all;
      PR(3);
      if (fast && !NOLD) {
        const uint4* src = &g_w[wg ^ (cta & 1)][0][threadIdx.x & 127];
        auto ld = [&](int i, uint32_t* w) {
          asm volatile("ld.relaxed.gpu.global.v4.u32 {%0,%1,%2,%3}, [%4];\n" : "=r"(w[0]), "=r"(w[1]), "=r"(w[2]), "=r"(w[3]) : "l"(src + i * 128) : "memory");
        };
#pragma unroll
        for (int i = 0; i < 12; i++) wQ[i] = wV[i];
#pragma unroll
        for (int s = 3; s < 8; s++) ld(s, wQ + 4 * s);
#pragma unroll
        for (int s = 0; s < 8; s++) ld(8 + s, wK + 4 * s);
#pragma unroll
        for (int s = 3; s < 8; s++) ld(13 + s, wV + 4 * s);
#pragma unroll
        for (int s = 0; s < 3; s++) ldsm_x4_t(t_addr + kWsOff + s * 2048, wV[4 * s], wV[4 * s + 1], wV[4 * s + 2], wV[4 * s + 3]);
      }
    }
    float sa, sb;
#pragma unroll
    for (int j = 0; j < DJ; j++) set_exp<0>(acc2, j, sa, tail_inv());
    sc = q3_dep(qc, acc2[4 * DJ - 3]);
    bool bad = out_of_range<FAST>(sc);
    const float ic = rcp(sc);
    {
      sd = fmaf(acc2[4 * DJ - 3], zf, sd) + sd2;
      bad |= out_of_range<FAST>(sd);
      const float id = rcp(sd);
      stsm_x2(wgb + kPOff + 12 * kPGrp + warp * 16 + ln * kPL, pack_bf16(x[0] * id, x[1] * id), pack_bf16(x[2] * id, x[3] * id));
    }
#pragma unroll
    for (int c = 0; c < 4; c++) norm_set<0>(acc1, c, ic, p8_addr() + 2 * kPGrp);
#pragma unroll
    for (int j = DJ; j < 13; j++) set_exp<0>(acc2, j, sa, tail_inv());
    const Q3 qa = q3_start(sa, 1);
    sched_barrier();
#pragma unroll
    for (int j = 0; j < DJ; j++) set_exp<2>(acc2, j, sb, tail_inv());
    sa = q3_dep(qa, acc2[4 * DJ - 1]);
    bad |= out_of_range<FAST>(sa);
    const float ia = rcp(sa);
#pragma unroll
    for (int c = 0; c < 4; c++) norm_set<0>(acc2, c, ia, p8_addr());
    constexpr int kRJ = FAST ? RJ : RJP;
#pragma unroll
    for (int j = DJ; j < kRJ; j++) set_exp<2>(acc2, j, sb, tail_inv());
    PIN(sb);
    sched_barrier();
    if (!FAST) mbar_wait(bar_w + 8 * (4 * wg + 3), 0);
    asm volatile("cp.async.bulk.wait_group.read 0;\n" ::: "memory");
    if (wg == 1 || it < n_tiles) bar_sync(3 + wg, 256);
    wg_fence();
    if (FAST) proj3_rs<true>(acc1, wV, dE); else proj3_ss(acc1, dE, dW);
    proj5_ss(acc1, dE, dW);
    wg_commit();
    sched_barrier();
#pragma unroll
    for (int j = kRJ; j < 13; j++) set_exp<2>(acc2, j, sb, tail_inv());
    sb = q3_end(q3_start(sb, 1));
    bad |= out_of_range<FAST>(sb);
    const float ib = rcp(sb);
#pragma unroll
    for (int c = 0; c < 4; c++) norm_set<2>(acc2, c, ib, p8_addr() + kPGrp);
    asm volatile("{.reg .pred p;\nsetp.ne.u32 p, %2, 0;\n@p red.shared.or.b32 [%0], %1;}\n" ::"r"(kS + kFlagOff + 4 * wg), "r"(1u << min(it, 31)), "r"((uint32_t)bad) : "memory");
    if (wg == 1 && warp == kRefill && ln == 0 && (FAST || it >= 1) && it + kStages - 2 < n_tiles) {
      const int ps = (it - 1) & (kStages - 1);
      if (!FAST && it == 1) load_r(row_of(3), 3, bar_full + 24);
      load_r(it + kStages - 1 < n_tiles ? row_of(it + kStages - 1) : lds(kS + kFlagOff + 12), ps, bar_full + 8 * ps);
    }
    wg_wait<0>();
    fence_acc(acc1);
    publish(wg);
    asm volatile("xor.b32 %0, %0, %1;\n" : "+r"(ln) : "r"(zero));
    if (!FAST && it == 0) PR(8);
  };
  auto slow = [&](auto wgc) __attribute__((always_inline)) {
    do iter(wgc, IC<0>()); while (!fast && (it + 1 < n_tiles || more(wgc)));
    PR(4);
  };
  auto quick = [&](auto wgc) __attribute__((always_inline)) {
    do iter(wgc, IC<1>()); while (it + 1 < n_tiles || more(wgc));
  };
  auto finish = [&](auto wgc) __attribute__((always_inline)) {
    const int wg = wgc;
    PR(9);
    wg_fence();
    issue_pv(acc1, vf, desc_p(kS + kWGBase + wg * kWGRegion + kPOff), z0, z1);
    wg_commit();
    if (wg == 0 && it < n_tiles) bar_arrive(4, 256);
    wg_wait<0>();
    fence_acc(acc1);
    store_t<true>(acc1, t_addr + kOOff);
    publish(wg);
    if (warp == kElect && ln == 0) tma_out(wg, it == n_tiles ? lds(kS + kFlagOff + 12) : row_of(it));
  };
  start(wg_r);
  if (wg_r == 0) { slow(IC<0>()); if (fast) quick(IC<0>()); } else { slow(IC<1>()); if (fast) quick(IC<1>()); }
  finish(wg_r);
  PR(11);
  if (tid == 64) mbar_wait(bar_full + 8 * (n_tiles & 3), (n_tiles >> 2) & 1);
  __syncthreads();
  if (lds(kS + kFlagOff) | lds(kS + kFlagOff + 4))
    exact_redo(&tm_e, &tm_o, &tm_q, &tm_k, &tm_v, it + 1, n_tiles, n_base, n_extra, lds(kS + kFlagOff + 4 * wg_r));
  if (warp == kElect && ln == 0) asm volatile("cp.async.bulk.wait_group.read 0;\n" ::: "memory");
}

typedef CUresult (*EncodeFn)(CUtensorMap*, CUtensorMapDataType, cuuint32_t, void*, const cuuint64_t*, const cuuint64_t*,
                             const cuuint32_t*, const cuuint32_t*, CUtensorMapInterleave, CUtensorMapSwizzle,
                             CUtensorMapL2promotion, CUtensorMapFloatOOBfill);

}

extern "C" void kernel_launch(void* const* d_in, const int* in_sizes, int n_in, void* d_out, int out_size) {
  static EncodeFn encode = nullptr;
  static int num_sms = 0;
  if (!encode) {
    void* fn = nullptr;
    cudaDriverEntryPointQueryResult qres;
    cudaGetDriverEntryPoint("cuTensorMapEncodeTiled", &fn, cudaEnableDefault, &qres);
    encode = (EncodeFn)fn;
    int dev = 0;
    cudaGetDevice(&dev);
    cudaDeviceGetAttribute(&num_sms, cudaDevAttrMultiProcessorCount, dev);
    cudaFuncSetAttribute(autoint_kernel, cudaFuncAttributeMaxDynamicSharedMemorySize, kSmemBytes);
  }
  auto make = [&](void* p, uint64_t cols, uint64_t rows, uint32_t box_rows, CUtensorMapL2promotion promo) {
    CUtensorMap tm;
    cuuint64_t dims[2] = {cols, rows};
    cuuint64_t strides[1] = {cols * 2};
    cuuint32_t box[2] = {64, box_rows};
    cuuint32_t estr[2] = {1, 1};
    encode(&tm, CU_TENSOR_MAP_DATA_TYPE_BFLOAT16, 2, p, dims, strides, box, estr, CU_TENSOR_MAP_INTERLEAVE_NONE,
           CU_TENSOR_MAP_SWIZZLE_128B, promo, CU_TENSOR_MAP_FLOAT_OOB_FILL_NONE);
    return tm;
  };
  const CUtensorMap tm_e = make(d_in[0], kD, (uint64_t)kB * kF, kF, CU_TENSOR_MAP_L2_PROMOTION_L2_256B);
  const CUtensorMap tm_o = make(d_out, kD, (uint64_t)kB * kF, kF, CU_TENSOR_MAP_L2_PROMOTION_NONE);
  const CUtensorMap tm_q = make(d_in[1], 64, 256, 128, CU_TENSOR_MAP_L2_PROMOTION_L2_256B);
  const CUtensorMap tm_k = make(d_in[2], 64, 256, 128, CU_TENSOR_MAP_L2_PROMOTION_L2_256B);
  const CUtensorMap tm_v = make(d_in[3], 64, 256, 128, CU_TENSOR_MAP_L2_PROMOTION_L2_256B);
  const CUtensorMap tm_r = make(d_in[4], 128, 128, 128, CU_TENSOR_MAP_L2_PROMOTION_L2_256B);
  const int grid = (num_sms < 2 ? 2 : num_sms < kB / 8 ? num_sms : kB / 8) & ~1;
  const int n_base = kB / grid, rem = kB - n_base * grid, split = 2 * (rem + 2 * SKIP) <= grid;
  autoint_kernel<<<grid, 256, kSmemBytes>>>(tm_e, tm_o, tm_q, tm_k, tm_v, tm_r, (const uint8_t*)d_in[0],
                                             WPtrs{{(const uint8_t*)d_in[1], (const uint8_t*)d_in[2], (const uint8_t*)d_in[3], (const uint8_t*)d_in[4]}},
                                             n_base, split ? 0 : rem, split ? SKIP : 0, 0, split ? rem + 2 * SKIP : 0);
}
```

```cpp
#include <cuda_runtime.h>
#include <cuda_bf16.h>
#include <cuda.h>
#include <stdint.h>

namespace {

constexpr int kB = 4096, kF = 100, kD = 128;
constexpr int kStages = 4;
constexpr int kElect = 3, kRefill = 2;
constexpr int kSwitch = 3;
constexpr int kSkip = 4;
constexpr uint32_t kS = 1024;
constexpr int kEHalf = 104 * 128;
constexpr int kEStage = 2 * kEHalf;
constexpr int kETx = 2 * kF * 128;
constexpr int kOOff = 0;
constexpr int kQOff = 13312;
constexpr int kKOff = kQOff + 16384;
constexpr int kPOff = kQOff;
constexpr int kPL = 144;
constexpr int kPGrp = 13 * kPL;
constexpr int kWsOff = kKOff + 13312;
constexpr int kWGRegion = kWsOff + 16384;
constexpr int kWGBase = kStages * kEStage;
constexpr int kBarOff = kWGBase + 2 * kWGRegion;
constexpr int kOpenOff = kBarOff + 256;
constexpr int kClaimOff = kBarOff + 272;
constexpr int kBadOff = kBarOff + 320;
constexpr int kPeekOff = kBarOff + 384;
constexpr int kTmpOff = kBarOff + 512;
constexpr int kSmemBytes = kTmpOff + 2 * 1024;
static_assert(kWGRegion % 1024 == 0 && kQOff % 1024 == 0 && kKOff % 1024 == 0 && kWsOff % 1024 == 0 && kWGBase % 1024 == 0 &&
              kPOff + 12 * kPGrp + 16 * kPL <= kWsOff && kSmemBytes <= 232448, "smem layout");

__device__ unsigned g_claim[512];
__device__ uint4 g_w[2][13][128];
__device__ __align__(16) unsigned g_state[4];
__device__ unsigned g_seen, g_epoch;

__device__ __forceinline__ uint32_t smem_u32(const void* p) { return (uint32_t)__cvta_generic_to_shared(p); }

__device__ __forceinline__ void wg_fence() { asm volatile("wgmma.fence.sync.aligned;\n" ::: "memory"); }
__device__ __forceinline__ void wg_commit() { asm volatile("wgmma.commit_group.sync.aligned;\n" ::: "memory"); }
template <int N> __device__ __forceinline__ void wg_wait() { asm volatile("wgmma.wait_group.sync.aligned %0;\n" ::"n"(N) : "memory"); }
__device__ __forceinline__ void fence_async() { asm volatile("fence.proxy.async.shared::cta;\n" ::: "memory"); }
__device__ __forceinline__ void bar_sync(int id, int n) { asm volatile("bar.sync %0, %1;\n" ::"r"(id), "r"(n) : "memory"); }
__device__ __forceinline__ void bar_arrive(int id, int n) { asm volatile("bar.arrive %0, %1;\n" ::"r"(id), "r"(n) : "memory"); }

#define ACC_REGS "{%0,%1,%2,%3,%4,%5,%6,%7,%8,%9,%10,%11,%12,%13,%14,%15,%16,%17,%18,%19,%20,%21,%22,%23,%24,%25," \
                 "%26,%27,%28,%29,%30,%31,%32,%33,%34,%35,%36,%37,%38,%39,%40,%41,%42,%43,%44,%45,%46,%47,%48,%49,%50,%51}"
#define ACC_OPS(c, d)                                                                                        \
  c(d[0]), c(d[1]), c(d[2]), c(d[3]), c(d[4]), c(d[5]), c(d[6]), c(d[7]), c(d[8]), c(d[9]), c(d[10]),        \
  c(d[11]), c(d[12]), c(d[13]), c(d[14]), c(d[15]), c(d[16]), c(d[17]), c(d[18]), c(d[19]), c(d[20]),        \
  c(d[21]), c(d[22]), c(d[23]), c(d[24]), c(d[25]), c(d[26]), c(d[27]), c(d[28]), c(d[29]), c(d[30]),        \
  c(d[31]), c(d[32]), c(d[33]), c(d[34]), c(d[35]), c(d[36]), c(d[37]), c(d[38]), c(d[39]), c(d[40]),        \
  c(d[41]), c(d[42]), c(d[43]), c(d[44]), c(d[45]), c(d[46]), c(d[47]), c(d[48]), c(d[49]), c(d[50]), c(d[51])

#define H4(d, i) "+f"(d[i]), "+f"(d[i + 1]), "=f"(d[i + 2]), "=f"(d[i + 3])
#define ACC_HALF(d) H4(d, 0), H4(d, 4), H4(d, 8), H4(d, 12), H4(d, 16), H4(d, 20), H4(d, 24), H4(d, 28), H4(d, 32), H4(d, 36), H4(d, 40), H4(d, 44), H4(d, 48)

__device__ __forceinline__ void fence_acc(float (&d)[52]) {
  asm volatile("" : ACC_OPS("+f", d)::"memory");
}

template <bool ACC>
__device__ __forceinline__ void mma_rs(float (&d)[52], uint32_t a0, uint32_t a1, uint32_t a2, uint32_t a3, uint64_t db) {
  if constexpr (ACC) {
    asm volatile("wgmma.mma_async.sync.aligned.m64n104k16.f32.bf16.bf16 " ACC_REGS
                 ", {%52,%53,%54,%55}, %56, 1, 1, 1, 0;\n"
                 : ACC_OPS("+f", d)
                 : "r"(a0), "r"(a1), "r"(a2), "r"(a3), "l"(db));
  } else {
    asm volatile("wgmma.mma_async.sync.aligned.m64n104k16.f32.bf16.bf16 " ACC_REGS
                 ", {%52,%53,%54,%55}, %56, 0, 1, 1, 0;\n"
                 : ACC_OPS("=f", d)
                 : "r"(a0), "r"(a1), "r"(a2), "r"(a3), "l"(db));
  }
}
__device__ __forceinline__ void mma_ss(float (&d)[52], uint64_t da, uint64_t db) {
  asm volatile("wgmma.mma_async.sync.aligned.m64n104k16.f32.bf16.bf16 " ACC_REGS ", %52, %53, 1, 1, 1, 0, 0;\n"
               : ACC_OPS("+f", d)
               : "l"(da), "l"(db));
}
__device__ __forceinline__ void mma_ss_tied(float (&d)[52], uint64_t da, uint64_t db) {
  asm volatile("wgmma.mma_async.sync.aligned.m64n104k16.f32.bf16.bf16 " ACC_REGS ", %52, %53, 0, 1, 1, 0, 0;\n"
               : ACC_OPS("+f", d)
               : "l"(da), "l"(db));
}
template <bool ACC>
__device__ __forceinline__ void mma_ss_ta(float (&d)[52], uint64_t da, uint64_t db) {
  if constexpr (ACC) {
    asm volatile("wgmma.mma_async.sync.aligned.m64n104k16.f32.bf16.bf16 " ACC_REGS ", %52, %53, 1, 1, 1, 1, 0;\n"
                 : ACC_OPS("+f", d)
                 : "l"(da), "l"(db));
  } else {
    asm volatile("wgmma.mma_async.sync.aligned.m64n104k16.f32.bf16.bf16 " ACC_REGS ", %52, %53, 0, 1, 1, 1, 0;\n"
                 : ACC_OPS("=f", d)
                 : "l"(da), "l"(db));
  }
}

__device__ __forceinline__ void mma_ss_ta_half(float (&d)[52], uint64_t da, uint64_t db) {
  asm volatile("wgmma.mma_async.sync.aligned.m64n104k16.f32.bf16.bf16 " ACC_REGS ", %52, %53, 0, 1, 1, 1, 0;\n"
               : ACC_HALF(d)
               : "l"(da), "l"(db));
}
__device__ __forceinline__ uint64_t desc_sw128(uint32_t saddr) {
  return (uint64_t)((saddr & 0x3FFFF) >> 4) | ((uint64_t)1 << 16) | ((uint64_t)(1024 >> 4) << 32) | ((uint64_t)1 << 62);
}
__device__ __forceinline__ uint64_t desc_p(uint32_t saddr) {
  return (uint64_t)((saddr & 0x3FFFF) >> 4) | ((uint64_t)(kPL >> 4) << 16) | ((uint64_t)(kPGrp >> 4) << 32);
}

__device__ __forceinline__ uint32_t pack_bf16(float lo, float hi) {
  uint32_t r;
  asm("cvt.rn.bf16x2.f32 %0, %1, %2;\n" : "=r"(r) : "f"(hi), "f"(lo));
  return r;
}
__device__ __forceinline__ uint32_t pack_bf16_relu(float lo, float hi) {
  uint32_t r;
  asm("cvt.rn.relu.bf16x2.f32 %0, %1, %2;\n" : "=r"(r) : "f"(hi), "f"(lo));
  return r;
}
__device__ __forceinline__ float ex2(float x) {
  float y;
  asm("ex2.approx.ftz.f32 %0, %1;\n" : "=f"(y) : "f"(x));
  return y;
}
__device__ __forceinline__ float rcp(float x) {
  float y;
  asm("rcp.approx.ftz.f32 %0, %1;\n" : "=f"(y) : "f"(x));
  return y;
}
__device__ __forceinline__ float rsq(float x) {
  float y;
  asm("rsqrt.approx.ftz.f32 %0, %1;\n" : "=f"(y) : "f"(x));
  return y;
}
__device__ __forceinline__ void stsm_x4(uint32_t addr, uint32_t r0, uint32_t r1, uint32_t r2, uint32_t r3) {
  asm volatile("stmatrix.sync.aligned.m8n8.x4.shared.b16 [%0], {%1,%2,%3,%4};\n" ::"r"(addr), "r"(r0), "r"(r1), "r"(r2), "r"(r3) : "memory");
}
__device__ __forceinline__ void stsm_x2(uint32_t addr, uint32_t r0, uint32_t r1) {
  asm volatile("stmatrix.sync.aligned.m8n8.x2.shared.b16 [%0], {%1,%2};\n" ::"r"(addr), "r"(r0), "r"(r1) : "memory");
}
__device__ __forceinline__ void stsm_x1(uint32_t addr, uint32_t r0) {
  asm volatile("stmatrix.sync.aligned.m8n8.x1.shared.b16 [%0], {%1};\n" ::"r"(addr), "r"(r0) : "memory");
}
__device__ __forceinline__ void stsm_x4_t(uint32_t addr, uint32_t r0, uint32_t r1, uint32_t r2, uint32_t r3) {
  asm volatile("stmatrix.sync.aligned.m8n8.x4.trans.shared.b16 [%0], {%1,%2,%3,%4};\n" ::"r"(addr), "r"(r0), "r"(r1), "r"(r2), "r"(r3) : "memory");
}
__device__ __forceinline__ void stsm_x2_t(uint32_t addr, uint32_t r0, uint32_t r1) {
  asm volatile("stmatrix.sync.aligned.m8n8.x2.trans.shared.b16 [%0], {%1,%2};\n" ::"r"(addr), "r"(r0), "r"(r1) : "memory");
}
__device__ __forceinline__ void ldsm_x4_t(uint32_t addr, uint32_t& r0, uint32_t& r1, uint32_t& r2, uint32_t& r3) {
  asm volatile("ldmatrix.sync.aligned.m8n8.x4.trans.shared.b16 {%0,%1,%2,%3}, [%4];\n" : "=r"(r0), "=r"(r1), "=r"(r2), "=r"(r3) : "r"(addr) : "memory");
}
__device__ __forceinline__ int lds16(uint32_t addr) {
  uint16_t v;
  asm volatile("ld.shared.u16 %0, [%1];\n" : "=h"(v) : "r"(addr) : "memory");
  return v;
}
__device__ __forceinline__ int lds(uint32_t addr) {
  int v;
  asm volatile("ld.shared.u32 %0, [%1];\n" : "=r"(v) : "r"(addr) : "memory");
  return v;
}
__device__ __forceinline__ int4 lds4(uint32_t addr) {
  int4 v;
  asm volatile("ld.shared.v4.u32 {%0,%1,%2,%3}, [%4];\n" : "=r"(v.x), "=r"(v.y), "=r"(v.z), "=r"(v.w) : "r"(addr) : "memory");
  return v;
}
__device__ __forceinline__ void sts(uint32_t addr, int v) { asm volatile("st.shared.u32 [%0], %1;\n" ::"r"(addr), "r"(v) : "memory"); }
__device__ __forceinline__ void sts4(uint32_t addr, int x, int y, int z, int w) {
  asm volatile("st.shared.v4.u32 [%0], {%1,%2,%3,%4};\n" ::"r"(addr), "r"(x), "r"(y), "r"(z), "r"(w) : "memory");
}
__device__ __forceinline__ void mbar_init(uint32_t bar, int count) {
  asm volatile("mbarrier.init.shared::cta.b64 [%0], %1;\n" ::"r"(bar), "r"(count) : "memory");
}
__device__ __forceinline__ void mbar_expect_tx(uint32_t bar, int bytes) {
  asm volatile("mbarrier.arrive.expect_tx.shared::cta.b64 _, [%0], %1;\n" ::"r"(bar), "r"(bytes) : "memory");
}
__device__ __forceinline__ void mbar_wait(uint32_t bar, uint32_t parity) {
  asm volatile(
      "{\n.reg .pred p;\n"
      "WAIT_%=:\n"
      "mbarrier.try_wait.parity.shared::cta.b64 p, [%0], %1;\n"
      "@p bra DONE_%=;\n"
      "bra WAIT_%=;\n"
      "DONE_%=:\n}\n" ::"r"(bar), "r"(parity) : "memory");
}
__device__ __forceinline__ void tma_load_2d(uint32_t dst, const CUtensorMap* tm, int c0, int c1, uint32_t bar) {
  asm volatile("cp.async.bulk.tensor.2d.shared::cluster.global.mbarrier::complete_tx::bytes [%0], [%1, {%3, %4}], [%2];\n" ::"r"(dst),
               "l"(tm), "r"(bar), "r"(c0), "r"(c1) : "memory");
}
__device__ __forceinline__ void tma_store_2d(const CUtensorMap* tm, uint32_t src, int c0, int c1) {
  asm volatile("cp.async.bulk.tensor.2d.global.shared::cta.bulk_group [%0, {%2, %3}], [%1];\n" ::"l"(tm), "r"(src), "r"(c0), "r"(c1) : "memory");
}

__device__ __forceinline__ void mma_rs_tied(float (&d)[52], uint32_t a0, uint32_t a1, uint32_t a2, uint32_t a3, uint64_t db) {
  asm volatile("wgmma.mma_async.sync.aligned.m64n104k16.f32.bf16.bf16 " ACC_REGS ", {%52,%53,%54,%55}, %56, 0, 1, 1, 0;\n"
               : ACC_OPS("+f", d)
               : "r"(a0), "r"(a1), "r"(a2), "r"(a3), "l"(db));
}
template <bool TIED = false>
__device__ __forceinline__ void proj(float (&acc)[52], const uint32_t (&w)[32], uint64_t de) {
#pragma unroll
  for (int s = 0; s < 8; s++) {
    uint64_t db = de + (uint64_t)(((s >> 2) * kEHalf + (s & 3) * 32) >> 4);
    if (s == 0) { if (TIED) mma_rs_tied(acc, w[0], w[1], w[2], w[3], db); else mma_rs<false>(acc, w[0], w[1], w[2], w[3], db); }
    else mma_rs<true>(acc, w[4 * s], w[4 * s + 1], w[4 * s + 2], w[4 * s + 3], db);
  }
}
__device__ __forceinline__ void proj_v(float (&acc)[52], const uint32_t (&w)[32], uint64_t de) {
#pragma unroll
  for (int s = 3; s < 8; s++) {
    uint64_t db = de + (uint64_t)(((s >> 2) * kEHalf + (s & 3) * 32) >> 4);
    mma_rs<true>(acc, w[4 * s], w[4 * s + 1], w[4 * s + 2], w[4 * s + 3], db);
  }
}
__device__ __forceinline__ void mma_rs_half(float (&d)[52], uint32_t a0, uint32_t a1, uint32_t a2, uint32_t a3, uint64_t db) {
  asm volatile("wgmma.mma_async.sync.aligned.m64n104k16.f32.bf16.bf16 " ACC_REGS ", {%52,%53,%54,%55}, %56, 0, 1, 1, 0;\n"
               : ACC_HALF(d)
               : "r"(a0), "r"(a1), "r"(a2), "r"(a3), "l"(db));
}
template <bool REGS, bool HALF>
__device__ __forceinline__ void proj_r(float (&acc)[52], const uint32_t* w, uint64_t de, uint64_t dw) {
#pragma unroll
  for (int s = 0; s < 8; s++) {
    uint64_t db = de + (uint64_t)(((s >> 2) * kEHalf + (s & 3) * 32) >> 4);
    if (REGS && s == 0) mma_rs_half(acc, w[0], w[1], w[2], w[3], db);
    else if (REGS && s < 3) mma_rs<true>(acc, w[4 * s], w[4 * s + 1], w[4 * s + 2], w[4 * s + 3], db);
    else if (s == 0) { if (HALF) mma_ss_ta_half(acc, dw, db); else mma_ss_ta<false>(acc, dw, db); }
    else mma_ss_ta<true>(acc, dw + (uint64_t)(s * 128), db);
  }
}

template <bool RELU>
__device__ __forceinline__ void store_t(const float (&a)[52], uint32_t addr) {
  auto pk = [&](int i) { return RELU ? pack_bf16_relu(a[i], a[i + 1]) : pack_bf16(a[i], a[i + 1]); };
#pragma unroll
  for (int j = 0; j < 12; j += 2) stsm_x4_t(addr + j * 1024, pk(4 * j), pk(4 * j + 2), pk(4 * j + 4), pk(4 * j + 6));
  stsm_x2_t(addr + 12 * 1024, pk(48), pk(50));
}
__device__ __forceinline__ void store_q_t(const float (&a)[52], uint32_t addr, uint32_t addr_hi, uint32_t addr_last, int src) {
  auto pk = [&](int i) { return pack_bf16(a[i], a[i + 1]); };
#pragma unroll
  for (int w = 0; w < 4; w++) {
    stsm_x4_t(addr + kQOff + 2 * w * 1024, pk(12 * w), pk(12 * w + 2), pk(12 * w + 4), pk(12 * w + 6));
    if (w & 1) stsm_x4_t(addr_hi + kQOff + (6 + 2 * w) * 1024, pk(12 * w - 4), pk(12 * w - 2), pk(12 * w + 8), pk(12 * w + 10));
  }
  const uint32_t r0 = __shfl_sync(0xffffffffu, pk(48), src), r1 = __shfl_sync(0xffffffffu, pk(50), src);
  stsm_x4_t(addr_last, r0, r1, r0, r1);
  stsm_x4_t(addr_last ^ 0x240, r0, r1, r0, r1);
}

constexpr float kC = 0.125f * 1.4426950408889634f;

__device__ __forceinline__ float quad_sum(float t) {
  t += __shfl_xor_sync(0xffffffffu, t, 1);
  t += __shfl_xor_sync(0xffffffffu, t, 2);
  return t;
}
#define PIN(x) asm volatile("" : "+f"(x)::"memory")
struct Q3 { float t, s1, s2, s3; };
__device__ __forceinline__ Q3 q3_start(float t, int m) {
  Q3 q;
  q.t = t;
  q.s1 = __shfl_xor_sync(0xffffffffu, t, m);
  q.s2 = __shfl_xor_sync(0xffffffffu, t, 2 * m);
  q.s3 = __shfl_xor_sync(0xffffffffu, t, 3 * m);
  return q;
}
__device__ __forceinline__ float q3_end(const Q3& q) { return (q.t + q.s1) + (q.s2 + q.s3); }
template <bool TIGHT> __device__ __forceinline__ bool out_of_range(float t) {
  return TIGHT ? !(t >= 0x1p-7f && t <= 0x1p12f) : !(t >= 0x1p-30f && t <= 0x1p30f);
}

template <int O> __device__ __forceinline__ void set_exp(float (&s)[52], int j, float& t, bool tail_invalid) {
  s[4 * j + O] = ex2(s[4 * j + O]);
  s[4 * j + O + 1] = ex2(s[4 * j + O + 1]);
  if (j == 0) t = s[O] + s[O + 1];
  else if (j < 12 || !tail_invalid) { t += s[4 * j + O]; t += s[4 * j + O + 1]; }
}
template <int O> __device__ __forceinline__ void norm_set(const float (&s)[52], int c, float iv, uint32_t paddr) {
  const int i = 16 * c + O;
  if (c < 3) stsm_x4(paddr + 4 * c * kPL, pack_bf16(s[i] * iv, s[i + 1] * iv), pack_bf16(s[i + 4] * iv, s[i + 5] * iv),
                     pack_bf16(s[i + 8] * iv, s[i + 9] * iv), pack_bf16(s[i + 12] * iv, s[i + 13] * iv));
  else stsm_x1(paddr + 12 * kPL, pack_bf16(s[48 + O] * iv, s[49 + O] * iv));
}
template <int O> __device__ __forceinline__ void set_exact(float (&s)[52], uint32_t paddr, bool tail_invalid) {
  if (tail_invalid) { s[48 + O] = -INFINITY; s[49 + O] = -INFINITY; }
  float m = fmaxf(s[O], s[O + 1]);
#pragma unroll
  for (int j = 1; j < 13; j++) m = fmaxf(m, fmaxf(s[4 * j + O], s[4 * j + O + 1]));
  m = fmaxf(m, __shfl_xor_sync(0xffffffffu, m, 1));
  m = fmaxf(m, __shfl_xor_sync(0xffffffffu, m, 2));
  float t;
#pragma unroll
  for (int j = 0; j < 13; j++) {
    s[4 * j + O] -= m; s[4 * j + O + 1] -= m;
    set_exp<O>(s, j, t, tail_invalid);
  }
  const float iv = rcp(quad_sum(t));
#pragma unroll
  for (int c = 0; c < 4; c++) norm_set<O>(s, c, iv, paddr);
}

__device__ __forceinline__ void sched_barrier() { asm volatile("pmevent 1;\n" ::: "memory"); }

__device__ __forceinline__ void scale_wq(uint32_t (&w)[32]) {
#pragma unroll
  for (int i = 0; i < 32; i++)
    asm("{.reg .b32 t;\nmul.rn.bf16x2 t, %0, %2;\nfma.rn.bf16x2 %0, %0, %1, t;}\n" : "+r"(w[i]) : "r"(0x3e393e39u), "r"(0xb9acb9acu));
}
__device__ __forceinline__ void issue_s(float (&a)[52], uint64_t dq, uint64_t dk) {
#pragma unroll
  for (int s = 0; s < 4; s++) {
    if (s == 0) mma_ss_tied(a, dq, dk);
    else mma_ss(a, dq + 2 * s, dk + 2 * s);
  }
}
__device__ __forceinline__ void issue_pv(float (&a)[52], const uint32_t (&vf)[26], uint64_t dp, uint32_t z0 = 0, uint32_t z1 = 0) {
#pragma unroll
  for (int s = 0; s < 6; s++) mma_rs<true>(a, vf[4 * s], vf[4 * s + 1], vf[4 * s + 2], vf[4 * s + 3], dp + (kPL / 8) * s);
  mma_rs<true>(a, vf[24], vf[25], z0, z1, (dp + (kPL / 8) * 6) & ~((uint64_t)0x3FFF << 16));
}

__device__ __forceinline__ void exact_redo(const CUtensorMap* tm_e, const CUtensorMap* tm_o, const CUtensorMap* tm_q,
                                        const CUtensorMap* tm_k, const CUtensorMap* tm_v, int n_iter, int n_tiles, int n_base, int n_extra,
                                           uint32_t flags) {
  constexpr uint32_t sbase = kS;
  auto zero = [&]() {
    uint32_t z;
    asm volatile("ld.volatile.shared.u32 %0, [%1];\n" : "=r"(z) : "r"(sbase + kF * 128) : "memory");
    return z;
  };
  const int tid = threadIdx.x + zero(), wg = tid >> 7, warp = (tid >> 5) & 3, lane = tid & 31;
  const int grid = gridDim.x, cta = blockIdx.x, head = wg ^ (cta & 1);
  const uint32_t wgb = sbase + kWGBase + wg * kWGRegion;
  const uint32_t bar_w = sbase + kBarOff + 64 + 32 * wg, bar_e = sbase + kBarOff + 128 + 8 * wg;
  const bool elected = warp == kElect && lane == 0;
  const bool tail_invalid = (lane & 2) != 0;
  const uint32_t t_addr = wgb + ((lane >> 4) * 8 + (lane & 7)) * 128 + (((2 * warp + ((lane >> 3) & 1)) ^ (lane & 7)) << 4);
  const uint32_t q12_k = (2 * (lane >> 4) + ((lane >> 2) & 1) + 2 * (lane & 3)) & 7;
  uint32_t q12_addr = wgb + kQOff + (9 + 2 * (lane & 3)) * 1024 + q12_k * 128 + (((2 * warp + ((lane >> 3) & 1)) ^ q12_k) << 4);
  const uint32_t p8_addr = wgb + kPOff + lane * 16 + (kPL - 128) / 8 * (lane & 24);
  auto e_desc = [&](int st) { return desc_sw128(sbase + (st + wg + zero()) * kEStage); };
  auto g_addr = [&]() { return wgb + zero(); };

  if (elected) {
    asm volatile("cp.async.bulk.wait_group 0;\n" ::: "memory");
    mbar_expect_tx(bar_w, 3 * 16384);
    tma_load_2d(wgb, tm_q, 0, head * 128, bar_w);
    tma_load_2d(wgb + 16384, tm_k, 0, head * 128, bar_w);
    tma_load_2d(sbase + (2 + wg) * kEStage, tm_v, 0, head * 128, bar_w);
  }
  mbar_wait(bar_w, 1);
  uint32_t wQ[32], wK[32], vf[26];
#pragma unroll
  for (int s = 0; s < 8; s++) {
    ldsm_x4_t(t_addr + s * 2048, wQ[4 * s], wQ[4 * s + 1], wQ[4 * s + 2], wQ[4 * s + 3]);
    ldsm_x4_t(t_addr + 16384 + s * 2048, wK[4 * s], wK[4 * s + 1], wK[4 * s + 2], wK[4 * s + 3]);
  }
  scale_wq(wQ);
  auto publish = [&]() {
    bar_sync(1 + wg, 128);
    fence_async();
  };
  bar_sync(1 + wg, 128);
  float acc1[52], acc2[52];
  uint32_t ph = 0;
  for (int t = 0; t < n_iter; t++) {
    if (!__any_sync(0xffffffffu, (flags >> min(t, 31)) & 1)) continue;
    const int row = t == n_tiles ? lds(sbase + kOpenOff + 4) : (t * grid + (t == 0 ? cta ^ head : t == n_base ? cta - grid + n_extra : cta)) * kF;
    if (elected) {
      mbar_expect_tx(bar_e, kETx);
      tma_load_2d(sbase + wg * kEStage, tm_e, 0, row, bar_e);
      tma_load_2d(sbase + wg * kEStage + kEHalf, tm_e, 64, row, bar_e);
    }
    mbar_wait(bar_e, ph);
    ph ^= 1;
    {
      const uint64_t dE = e_desc(0);
      wg_fence();
      proj(acc2, wQ, dE);
      proj(acc1, wK, dE);
      wg_commit();
    }
    wg_wait<0>();
    fence_acc(acc1);
    fence_acc(acc2);
    store_q_t(acc2, t_addr, t_addr + (lane >> 4) * 1024, q12_addr, lane & 29);
    store_t<false>(acc1, t_addr + kKOff);
    {
      const uint64_t dE = e_desc(0), dWv = e_desc(2);
      wg_fence();
      proj_r<false, false>(acc2, nullptr, dE, dWv);
      wg_commit();
    }
    wg_wait<0>();
    fence_acc(acc2);
#pragma unroll
    for (int i = 0; i < 26; i++) vf[i] = pack_bf16(acc2[2 * i], acc2[2 * i + 1]);
    publish();
    {
      const uint32_t g = g_addr();
      const uint64_t dQ = desc_sw128(g + kQOff), dK = desc_sw128(g + kKOff);
      wg_fence();
      issue_s(acc1, dQ, dK);
      issue_s(acc2, dQ + 512, dK);
      wg_commit();
    }
    wg_wait<0>();
    fence_acc(acc1);
    fence_acc(acc2);
    bar_sync(1 + wg, 128);
    set_exact<0>(acc1, p8_addr + 3 * warp * kPGrp, tail_invalid);
    set_exact<2>(acc1, p8_addr + (3 * warp + 1) * kPGrp, tail_invalid);
    set_exact<0>(acc2, p8_addr + (3 * warp + 2) * kPGrp, tail_invalid);
    set_exact<2>(acc2, wgb + kPOff + 12 * kPGrp + (lane >> 3) * kPL + warp * 16, tail_invalid);
    publish();
    {
      const uint32_t g = g_addr();
      const uint64_t dE = e_desc(0), dW = desc_sw128(g + kWsOff), dP = desc_p(g + kPOff);
      wg_fence();
      proj_r<false, false>(acc1, nullptr, dE, dW);
      issue_pv(acc1, vf, dP);
      wg_commit();
    }
    wg_wait<0>();
    fence_acc(acc1);
    store_t<true>(acc1, t_addr + kOOff);
    publish();
    if (elected) {
      tma_store_2d(tm_o, wgb + kOOff, head * 64, row);
      asm volatile("cp.async.bulk.commit_group;\n" ::: "memory");
      asm volatile("cp.async.bulk.wait_group 0;\n" ::: "memory");
    }
    bar_sync(1 + wg, 128);
  }
}

#define D32_REGS "{%0,%1,%2,%3,%4,%5,%6,%7,%8,%9,%10,%11,%12,%13,%14,%15,%16,%17,%18,%19,%20,%21,%22,%23,%24,%25,%26,%27,%28,%29,%30,%31}"
#define D32_OPS(c, d)                                                                                        \
  c(d[0]), c(d[1]), c(d[2]), c(d[3]), c(d[4]), c(d[5]), c(d[6]), c(d[7]), c(d[8]), c(d[9]), c(d[10]),        \
  c(d[11]), c(d[12]), c(d[13]), c(d[14]), c(d[15]), c(d[16]), c(d[17]), c(d[18]), c(d[19]), c(d[20]),        \
  c(d[21]), c(d[22]), c(d[23]), c(d[24]), c(d[25]), c(d[26]), c(d[27]), c(d[28]), c(d[29]), c(d[30]), c(d[31])
template <int ACC, int SA, int T>
__device__ __forceinline__ void mma64_ss(float (&d)[32], uint64_t da, uint64_t db) {
  if constexpr (ACC)
    asm volatile("wgmma.mma_async.sync.aligned.m64n64k16.f32.bf16.bf16 " D32_REGS ", %32, %33, 1, %34, 1, %35, %35;\n"
                 : D32_OPS("+f", d) : "l"(da), "l"(db), "n"(SA), "n"(T));
  else
    asm volatile("wgmma.mma_async.sync.aligned.m64n64k16.f32.bf16.bf16 " D32_REGS ", %32, %33, 0, %34, 1, %35, %35;\n"
                 : D32_OPS("=f", d) : "l"(da), "l"(db), "n"(SA), "n"(T));
}
template <int ACC, int T>
__device__ __forceinline__ void mma64_rs(float (&d)[32], const uint32_t* a, uint64_t db) {
  if constexpr (ACC)
    asm volatile("wgmma.mma_async.sync.aligned.m64n64k16.f32.bf16.bf16 " D32_REGS ", {%32,%33,%34,%35}, %36, 1, 1, 1, %37;\n"
                 : D32_OPS("+f", d) : "r"(a[0]), "r"(a[1]), "r"(a[2]), "r"(a[3]), "l"(db), "n"(T));
  else
    asm volatile("wgmma.mma_async.sync.aligned.m64n64k16.f32.bf16.bf16 " D32_REGS ", {%32,%33,%34,%35}, %36, 0, 1, 1, %37;\n"
                 : D32_OPS("=f", d) : "r"(a[0]), "r"(a[1]), "r"(a[2]), "r"(a[3]), "l"(db), "n"(T));
}
__device__ __forceinline__ void mma64_done(float (&d)[32]) {
  wg_commit();
  wg_wait<0>();
  asm volatile("" : D32_OPS("+f", d)::"memory");
}
__device__ __forceinline__ float bf_lo(uint32_t x) { return __uint_as_float(x << 16); }
__device__ __forceinline__ float bf_hi(uint32_t x) { return __uint_as_float(x & 0xffff0000u); }
__device__ __forceinline__ void split2(float x, float y, uint32_t& hi, uint32_t& lo) {
  hi = pack_bf16(x, y);
  lo = pack_bf16(x - bf_lo(hi), y - bf_hi(hi));
}
__device__ __forceinline__ float ldsf(uint32_t a) { return __int_as_float(lds(a)); }
__device__ __forceinline__ float2 ldsf2(uint32_t a) {
  float2 v;
  asm volatile("ld.shared.v2.f32 {%0,%1}, [%2];\n" : "=f"(v.x), "=f"(v.y) : "r"(a) : "memory");
  return v;
}
__device__ __forceinline__ float4 ldsf4(uint32_t a) {
  float4 v;
  asm volatile("ld.shared.v4.f32 {%0,%1,%2,%3}, [%4];\n" : "=f"(v.x), "=f"(v.y), "=f"(v.z), "=f"(v.w) : "r"(a) : "memory");
  return v;
}
__device__ __forceinline__ void stsf2(uint32_t a, float x, float y) { asm volatile("st.shared.v2.f32 [%0], {%1,%2};\n" ::"r"(a), "f"(x), "f"(y) : "memory"); }
__device__ __forceinline__ float warp_sum(float t) {
#pragma unroll
  for (int m = 1; m < 32; m *= 2) t += __shfl_xor_sync(0xffffffffu, t, m);
  return t;
}

template <class F>
__device__ __forceinline__ void transform_weights(int zero, int z, int warp, unsigned epoch, F late_loads) {
  const int t = (threadIdx.x + zero) & 127, lane = t & 31, q = lane & 3, r = 16 * warp + (lane >> 2);
  constexpr uint32_t kWq = kS + kWGBase, kWk = kWq + 16384, kWv = kS + kEStage;
  auto tile_hi = [](int s) { return kS + kWGBase + s * kWGRegion + 32768; };
  auto tile_lo = [](int s) { return kS + (1 + s) * kEStage + 16384; };
  const uint32_t tX = z ? kWv : kWq, tH = tile_hi(z), tL = tile_lo(z);
  const uint32_t big = kS + kWGBase + kWGRegion + z * 16384, gt = kS + z * kEHalf;
  const uint32_t n2 = kS + kTmpOff + z * 1024, buf = kS + 2 * kEStage + z * 1024;
  uint4* dst = &g_w[blockIdx.x][0][t] + (8 * z - 3) * 128;
  auto store_big = [&](const float (&d)[32]) {
#pragma unroll
    for (int g = 0; g < 8; g++) {
      const uint32_t a = big + r * 256 + ((g ^ (lane >> 2)) << 5) + 8 * q;
      stsf2(a, d[4 * g], d[4 * g + 1]);
      stsf2(a + 2048, d[4 * g + 2], d[4 * g + 3]);
    }
  };
#pragma unroll 1
  for (int i = 0; i < 5; i++) sts4(gt + 16 * t + 2048 * i, 0, 0, 0, 0);
  mbar_wait(kS + kBarOff + 64 + 16 * z, 0);
  float d[32];
  wg_fence();
#pragma unroll
  for (int s = 0; s < 4; s++) {
    if (s == 0) mma64_ss<0, 1, 0>(d, desc_sw128(tX), desc_sw128(tX));
    else mma64_ss<1, 1, 0>(d, desc_sw128(tX) + 2 * s, desc_sw128(tX) + 2 * s);
  }
  mma64_done(d);
  store_big(d);
  bar_sync(1 + z, 128);
  bool ok = true;
  {
    const int a = (t >> 4) * 2 + (t & 1), b = (t >> 1) & 7;
    float m[3][6], rs[3], cs[6];
    auto diag = [&](int i) { return rsq(ldsf(big + i * 256 + ((4 * i) ^ ((i & 7) << 5)))); };
#pragma unroll
    for (int i = 0; i < 3; i++) {
      rs[i] = diag(a + 16 * i); cs[2 * i] = diag(2 * b + 16 * i); cs[2 * i + 1] = diag(2 * b + 16 * i + 1);
#pragma unroll
      for (int j = 0; j < 3; j++) {
        const float2 v = ldsf2(big + (a + 16 * i) * 256 + ((8 * b + 64 * j) ^ ((a & 7) << 5)));
        m[i][2 * j] = v.x; m[i][2 * j + 1] = v.y;
      }
    }
#pragma unroll
    for (int i = 0; i < 18; i++) m[i / 6][i % 6] *= rs[i / 6] * cs[i % 6];
    const uint32_t xa = buf + 8 * a, ya = buf + 16 * b;
    const float g0 = a == 2 * b ? 1.f : 0.f, g1 = a == 2 * b + 1 ? 1.f : 0.f;
    auto put = [&](bool own, int o) {
      if (own) {
        m[0][0] -= g0; m[0][1] -= g1;
#pragma unroll
        for (int i = 0; i < 3; i++) stsf2(xa + o + 128 * i, m[i][0], m[i][1]);
        m[0][0] -= g0; m[0][1] -= g1;
      }
    };
#pragma unroll 1
    for (int g = 0; g < 3; g++) {
      put(b == 0, 0);
#pragma unroll 1
      for (int p2 = 0; p2 < 8; p2 += 2) {
#pragma unroll
        for (int u = 0; u < 2; u++) {
          bar_sync(1 + z, 128);
          float4 pv = ldsf4(buf + 16 * p2 + 528 * u), y[3];
          float2 x[3];
#pragma unroll
          for (int i = 0; i < 3; i++) x[i] = ldsf2(xa + 512 * u + 128 * i);
#pragma unroll
          for (int i = 0; i < 3; i++) y[i] = ldsf4(ya + 512 * u + 128 * i);
          pv.x += 1.f; pv.w += 1.f;
          const float id = rcp(pv.x * pv.w - pv.y * pv.y);
          float w[3][2];
#pragma unroll
          for (int i = 0; i < 3; i++) { w[i][0] = (x[i].y * pv.y - x[i].x * pv.w) * id; w[i][1] = (x[i].x * pv.y - x[i].y * pv.x) * id; }
#pragma unroll
          for (int j = 0; j < 3; j++) {
#pragma unroll
            for (int i = 0; i < 3; i++) {
              m[i][2 * j] = fmaf(w[i][0], y[j].x, fmaf(w[i][1], y[j].y, m[i][2 * j]));
              m[i][2 * j + 1] = fmaf(w[i][0], y[j].z, fmaf(w[i][1], y[j].w, m[i][2 * j + 1]));
            }
            if (j == 0) put(b == p2 + u + 1, 512 - 512 * u);
          }
        }
      }
      float o[3][6];
#pragma unroll
      for (int i = 0; i < 18; i++) o[i / 6][i % 6] = m[(i / 6 + 1) % 3][(i % 6 + 2) % 6];
#pragma unroll
      for (int i = 0; i < 18; i++) m[i / 6][i % 6] = o[i / 6][i % 6];
    }
#pragma unroll
    for (int i = 0; i < 3; i++) {
#pragma unroll
      for (int j = 0; j < 3; j++) {
        ok &= fabsf(m[i][2 * j]) <= 32.f;
        ok &= fabsf(m[i][2 * j + 1]) <= 32.f;
        uint32_t hi, lo;
        split2(-rs[i] * cs[2 * j] * m[i][2 * j], -rs[i] * cs[2 * j + 1] * m[i][2 * j + 1], hi, lo);
        const uint32_t o = (a + 16 * i) * 128 + ((4 * b + 32 * j) ^ ((a & 7) << 4));
        sts(tH + o, hi);
        sts(tL + o, lo);
      }
    }
  }
  mbar_wait(kS + kBarOff + 64 + 8, 0);
  mbar_wait(kS + kBarOff + 64 + 16 - 16 * z, 0);
  fence_async();
  bar_sync(1 + z, 128);
  wg_fence();
#pragma unroll
  for (int s = 0; s < 3; s++) {
    if (s == 0) mma64_ss<0, 1, 1>(d, desc_sw128(tH), desc_sw128(tX));
    else mma64_ss<1, 1, 1>(d, desc_sw128(tH) + 128 * s, desc_sw128(tX) + 128 * s);
    mma64_ss<1, 1, 1>(d, desc_sw128(tL) + 128 * s, desc_sw128(tX) + 128 * s);
  }
  mma64_done(d);
  uint32_t fh[16], fl[16];
  auto split_d = [&]() {
#pragma unroll
    for (int i = 0; i < 16; i++) split2(d[2 * i], d[2 * i + 1], fh[i], fl[i]);
  };
  split_d();
  bar_sync(1 + z, 128);
#pragma unroll
  for (int g = 0; g < 4; g++) {
    const uint32_t c = (16 * warp + (lane & 15)) * 128 + (((2 * g + (lane >> 4)) ^ (lane & 7)) << 4);
    stsm_x4(tH + c, fh[4 * g], fh[4 * g + 1], fh[4 * g + 2], fh[4 * g + 3]);
    stsm_x4(tL + c, fl[4 * g], fl[4 * g + 1], fl[4 * g + 2], fl[4 * g + 3]);
  }
  fence_async();
  bar_sync(1 + z, 128);
  wg_fence();
#pragma unroll
  for (int s = 0; s < 3; s++) {
    if (s == 0) mma64_ss<0, -1, 1>(d, desc_sw128(tX), desc_sw128(tH));
    else mma64_ss<1, -1, 1>(d, desc_sw128(tX) + 128 * s, desc_sw128(tH) + 128 * s);
    mma64_ss<1, -1, 1>(d, desc_sw128(tX) + 128 * s, desc_sw128(tL) + 128 * s);
  }
  wg_commit();
  float dm[32];
  auto mm = [&](uint32_t x, uint32_t y, bool first) {
    const uint64_t da = desc_sw128(z ? y : x), db = desc_sw128(z ? x : y);
    if (first) mma64_ss<0, 1, 1>(dm, da, db); else mma64_ss<1, 1, 1>(dm, da, db);
  };
#pragma unroll
  for (int s = 0; s < 3; s++) { mm(kWq + kWv - tX + 2048 * s, tH + 2048 * s, s == 0); mm(kWq + kWv - tX + 2048 * s, tL + 2048 * s, false); }
  wg_commit();
  wg_wait<1>();
  asm volatile("" : D32_OPS("+f", d)::"memory");
  store_big(d);
  bar_sync(1 + z, 128);
  if (warp == z) {
    const uint32_t da = big + lane * 512 + ((8 * lane) ^ ((lane & 3) << 6)), db = (da ^ 32) + 260;
    float dx = ldsf(da) + 1.f, dy = ldsf(db) + 1.f;
    sts(da, __float_as_int(dx));
    sts(db, __float_as_int(dy));
    float hx[16], hy[16];
#pragma unroll
    for (int i = 0; i < 16; i++) hx[i] = hy[i] = 0.f;
#pragma unroll 1
    for (int c = 0; c < 16; c += 4) {
#pragma unroll
      for (int e = 3; e >= 0; e--) {
        __syncwarp();
        const int key = __reduce_max_sync(0xffffffffu, max((__float_as_int(dx) & ~63) | (2 * lane), (__float_as_int(dy) & ~63) | (2 * lane + 1)));
        const int p = key & 63;
        const float2 row = ldsf2(big + p * 256 + ((8 * lane) ^ ((p & 7) << 5)));
        float k[16];
#pragma unroll
        for (int i = e == 3; i < 4; i++) {
          const float4 v = ldsf4(gt + p * 144 + 48 - 4 * c + 16 * i);
          k[4 * i] = v.x; k[4 * i + 1] = v.y; k[4 * i + 2] = v.z; k[4 * i + 3] = v.w;
        }
        const float is = rsq(__int_as_float(key));
        float ux[4] = {row.x, 0.f, 0.f, 0.f}, uy[4] = {row.y, 0.f, 0.f, 0.f};
#pragma unroll
        for (int i = e + 1; i < 16; i++) { ux[i >> 2] = fmaf(-k[i], hx[i], ux[i >> 2]); uy[i >> 2] = fmaf(-k[i], hy[i], uy[i >> 2]); }
        hx[e] = ((ux[0] + ux[1]) + (ux[2] + ux[3])) * is;
        hy[e] = ((uy[0] + uy[1]) + (uy[2] + uy[3])) * is;
        dx = fmaf(-hx[e], hx[e], dx);
        dy = fmaf(-hy[e], hy[e], dy);
        sts(gt + lane * 288 + 48 - 4 * c + 4 * e, __float_as_int(hx[e]));
        sts(gt + lane * 288 + 192 - 4 * c + 4 * e, __float_as_int(hy[e]));
        ok &= key >= 0x3c000000;
      }
#pragma unroll
      for (int i = 15; i >= 4; i--) { hx[i] = hx[i - 4]; hy[i] = hy[i - 4]; }
    }
    ok &= fmaxf(fabsf(dx), fabsf(dy)) <= 0x1p-10f;
  } else if (warp >= 2) {
#pragma unroll 1
    for (int h = 0; h < 2; h++) {
      const int row = (t & 63) + 64 * h;
      float a = 0.f, b = 0.f;
#pragma unroll 2
      for (int c = 0; c < 8; c++) {
        const int4 v = lds4(tX + row * 128 + ((c ^ (t & 7)) << 4));
        const uint32_t w[4] = {(uint32_t)v.x, (uint32_t)v.y, (uint32_t)v.z, (uint32_t)v.w};
#pragma unroll
        for (int k = 0; k < 4; k++) { a = fmaf(bf_lo(w[k]), bf_lo(w[k]), a); b = fmaf(bf_hi(w[k]), bf_hi(w[k]), b); }
      }
      sts(n2 + 4 * row, __float_as_int(a + b));
    }
    bar_sync(8 + z, 64);
    const float s = warp_sum(ldsf(n2 + 4 * lane) + (lane < 16 ? ldsf(n2 + 128 + 4 * lane) : 0.f)) * (1.f / 48);
    if (t == 64) sts(n2 + 1020, __float_as_int(s));
  }
  bar_sync(1 + z, 128);
  const float s2 = ldsf(n2 + 1020);
  ok &= (s2 >= 0x1p-60f) & (s2 <= 0x1p60f);
  {
    const float4 gx = ldsf4(gt + lane * 288 + 16 * warp), gy = ldsf4(gt + lane * 288 + 144 + 16 * warp);
    const float vx[4] = {gx.x, gx.y, gx.z, gx.w}, vy[4] = {gy.x, gy.y, gy.z, gy.w};
    float k = rsq(s2);
#pragma unroll 1
    for (int h = 0; h < 2; h++) {
#pragma unroll
      for (int i = 0; i < 4; i++) {
        uint32_t hi, lo;
        const uint32_t o = 6144 + 2048 * h + (4 * warp + i) * 128 + ((4 * lane) ^ (((4 * warp + i) & 7) << 4));
        split2(vx[i] * k, vy[i] * k, hi, lo);
        sts(tH + o, hi);
        sts(tL + o, lo);
      }
      k *= s2;
    }
  }
  fence_async();
  __syncthreads();
  wg_fence();
  mm(tile_hi(1 - z) + 8192, tH + 6144, false); mm(tile_hi(1 - z) + 8192, tL + 6144, false); mm(tile_lo(1 - z) + 8192, tH + 6144, false);
  wg_commit();
  const float so = ldsf(kS + kTmpOff + (1 - z) * 1024 + 1020);
  ok &= z | (ldsf(kS + kTmpOff + 4 * t) * so <= 6.f * s2 * ldsf(kS + kTmpOff + 1024 + 4 * t));
  wg_wait<0>();
  asm volatile("" : D32_OPS("+f", dm)::"memory");
  float nn = 0.f;
#pragma unroll
  for (int i = 0; i < 32; i++) { nn = fmaf(dm[i], dm[i], nn); d[i] = dm[i] * (z ? kC : 1.f); }
  split_d();
  {
    const uint64_t db = desc_sw128(z ? kWk : kWq);
    float d2[32];
    wg_fence();
#pragma unroll
    for (int s = 0; s < 4; s++) {
      if (s == 0) mma64_rs<0, 0>(d2, fh, db + 512); else mma64_rs<1, 0>(d2, fh + 4 * s, db + 512 + 2 * s);
      mma64_rs<1, 0>(d2, fl + 4 * s, db + 512 + 2 * s);
    }
    wg_commit();
#pragma unroll
    for (int s = 0; s < 4; s++) {
      if (s == 0) mma64_rs<0, 0>(d, fh, db); else mma64_rs<1, 0>(d, fh + 4 * s, db + 2 * s);
      mma64_rs<1, 0>(d, fl + 4 * s, db + 2 * s);
    }
    wg_commit();
    late_loads();
    auto out = [&](const float* x, int s) {
      if (s >= 3 || z) dst[s * 128] = make_uint4(pack_bf16(x[0], x[1]), pack_bf16(x[2], x[3]), pack_bf16(x[4], x[5]), pack_bf16(x[6], x[7]));
    };
    wg_wait<1>();
    asm volatile("" : D32_OPS("+f", d2)::"memory");
#pragma unroll
    for (int s = 0; s < 4; s++) out(d2 + 8 * s, 4 + s);
    wg_wait<0>();
    asm volatile("" : D32_OPS("+f", d)::"memory");
#pragma unroll
    for (int s = 0; s < 4; s++) out(d + 8 * s, s);
  }
  ok &= warp_sum(nn) * s2 <= 128.f * so;
  const int all = __syncthreads_and(ok);
  if (t == 64 && z == 1) asm volatile("st.release.gpu.global.u32 [%0], %1;\n" ::"l"(g_state + blockIdx.x), "r"(2 * epoch + 2 + (all != 0)) : "memory");
}

template <int V> struct IC { __device__ constexpr operator int() const { return V; } };
struct WPtrs { const uint8_t* p[4]; };

__global__ void __launch_bounds__(256, 1)
autoint_kernel(const __grid_constant__ CUtensorMap tm_e, const __grid_constant__ CUtensorMap tm_o,
               const __grid_constant__ CUtensorMap tm_q, const __grid_constant__ CUtensorMap tm_k,
               const __grid_constant__ CUtensorMap tm_v, const __grid_constant__ CUtensorMap tm_r,
               const uint8_t* p_e, const __grid_constant__ WPtrs pw,
               const int n_base, const int n_extra, const int n_skip, const int zero, const int n_open) {
  extern __shared__ __align__(1024) uint8_t smem[];
  const int tid = threadIdx.x;
  if ((tid & 31) == 0 && tid >= 64) asm volatile("prefetch.tensormap [%0];\n" ::"l"((const char*)&tm_e + (tid - 64) * 4) : "memory");
  if (tid < 200) asm volatile("prefetch.global.L2 [%0];\n" ::"l"(p_e + (blockIdx.x & ~1u) * (kF * kD * 2) + tid * 128) : "memory");
  else if (tid < 208) asm volatile("prefetch.global.L2 [%0];\n" ::"l"(pw.p[(blockIdx.x >> 5) & 3] + (blockIdx.x & 31) * 1024 + (tid & 7) * 128) : "memory");
  constexpr uint32_t bar_full = kS + kBarOff;
  constexpr uint32_t bar_w = kS + kBarOff + 64;
  const int grid = gridDim.x, cta = blockIdx.x;
  const int n_tiles = n_base + (cta >= grid - n_extra) - (cta < 2 ? n_skip : 0);
  auto row_of = [&](int t) { return (t * grid + cta - (t == n_base ? grid - n_extra : 0)) * kF; };
  auto load_r = [&](int row, int st, uint32_t bar) {
    mbar_expect_tx(bar, kETx);
    tma_load_2d(kS + st * kEStage, &tm_e, 0, row, bar);
    tma_load_2d(kS + st * kEStage + kEHalf, &tm_e, 64, row, bar);
  };

  auto load_w = [&](int w, int m) {
    const int h = w ^ (cta & 1);
    const uint32_t dst = kS + kWGBase + w * kWGRegion, bar = bar_w + 8 * (4 * w + m);
    mbar_expect_tx(bar, 16384);
    if (m == 0) tma_load_2d(dst, &tm_q, 0, h * 128, bar);
    if (m == 1) tma_load_2d(dst + 16384, &tm_k, 0, h * 128, bar);
    if (m == 2) tma_load_2d(kS + (1 + w) * kEStage, &tm_v, 0, h * 128, bar);
    if (m == 3) tma_load_2d(dst + kWsOff, &tm_r, h * 64, 0, bar);
  };
  if (tid == 0) {
    mbar_init(bar_w + 80, 1);
    mbar_init(bar_w, 1);
    mbar_init(bar_w + 8, 1);
    mbar_init(bar_w + 16, 1);
    asm volatile("fence.mbarrier_init.release.cluster;\n" ::: "memory");
    fence_async();
    load_w(0, 0); load_w(0, 1); load_w(0, 2);
    load_r((cta & ~1) * kF, 3, bar_w + 80);
  } else if (tid == 32) {
    if (smem_u32(smem) != kS) __trap();
    for (int s = 0; s < kStages; s++) mbar_init(bar_full + 8 * s, 1);
    for (int s = 3; s < 10; s++) mbar_init(bar_w + 8 * s, 1);
    for (int s = 0; s < 2; s++) mbar_init(bar_full + 32 + 8 * s, 1);
    asm volatile("fence.mbarrier_init.release.cluster;\n" ::: "memory");
  }
  const int wg_r = __shfl_sync(0xffffffffu, tid >> 7, 0);
  const int warp = __shfl_sync(0xffffffffu, (tid >> 5) & 3, 0);
  const int lane = tid & 31;
  auto st_zero = [&](uint32_t a) { asm volatile("st.shared.v4.u32 [%0], {%1,%1,%1,%1};\n" ::"r"(a), "r"(0) : "memory"); };
  if (tid >= 128) st_zero(kS + (warp + (warp & 2) * 2) * kEHalf + kF * 128 + lane * 16);
  fence_async();
  __syncthreads();
  auto loads2 = [&]() {
    if (tid == 128) {
      load_w(1, 0); load_w(1, 1); load_w(1, 2); load_w(0, 3);
      load_r((cta | 1) * kF, 0, bar_full);
      load_w(1, 3);
    }
  };
  if (cta >= 2) loads2();

  if (tid >= 224 && tid < 228) sts4(kS + kBadOff + 16 * (tid - 224), 0, 0, 0, 0);
  unsigned epoch = 0;
  if (tid == 192) epoch = *(volatile unsigned*)&g_epoch;
  if (tid == 160) {
    const int mod = max(n_open, 1), x = (cta >> 1) % mod, y = x - (n_open - 2 * n_skip);
    sts(kS + kOpenOff, 0);
    sts(kS + kOpenOff + 4, (n_open == 0 ? kB : y < 0 ? n_base * grid + x : (n_base - 1 - (y >> 1)) * grid + (y & 1)) * kF);
    const uint64_t ga = (uint64_t)__cvta_generic_to_global(g_claim + 2 * x + (cta & 1));
    sts4(kS + kClaimOff, (int)ga, (int)(ga >> 32), ((grid >> 1) - 1 - x) / mod, n_open ? n_tiles + 1 : 0);
  }
  if (cta < 2) transform_weights(zero, wg_r, warp, epoch, loads2);
  if (tid == 192) sts(kS + kOpenOff + 8, 2 * epoch + 2);

  int it = -1;
  bool fast = false;
  uint32_t ln = lane;
  uint32_t wQ[32], wK[32], wV[32], vf[26];
  float acc1[52], acc2[52];
  uint32_t z0 = 0, z1 = 0;
  uint32_t t_addr = kS + kWGBase + (tid >> 7) * kWGRegion + ((lane >> 4) * 8 + (lane & 7)) * 128 + (((2 * warp + ((lane >> 3) & 1)) ^ (lane & 7)) << 4);
  const uint32_t q12_k = (2 * (lane >> 4) + ((lane >> 2) & 1) + 2 * (lane & 3)) & 7;
  uint32_t q12_addr = kS + kWGBase + (tid >> 7) * kWGRegion + kQOff + (9 + 2 * (lane & 3)) * 1024 + q12_k * 128 + (((2 * warp + ((lane >> 3) & 1)) ^ q12_k) << 4);
  asm volatile("xor.b32 %0, %0, %2;\nxor.b32 %1, %1, %2;\n" : "+r"(t_addr), "+r"(q12_addr) : "r"(zero));
  auto tail_inv = [&]() { return (ln & 2) != 0; };
  auto publish = [&](int wg) {
    bar_sync(1 + wg, 128);
    fence_async();
  };
  auto tma_out = [&](int wg, int row) {
    tma_store_2d(&tm_o, kS + kWGBase + wg * kWGRegion + kOOff, (wg ^ (cta & 1)) * 64, row);
    asm volatile("cp.async.bulk.commit_group;\n" ::: "memory");
  };

  auto iter = [&](auto wgc, auto fastc) __attribute__((always_inline)) {
    constexpr bool FAST = fastc;
    constexpr int wg = wgc;
    constexpr int kLag = 3, kRJ = FAST ? 9 : 11;
    constexpr uint32_t wgb = kS + kWGBase + wg * kWGRegion, bar_peek = bar_full + 32 + 8 * wg;
    const uint64_t dQ = desc_sw128(wgb + kQOff), dK = desc_sw128(wgb + kKOff), dP = desc_p(wgb + kPOff), dW = desc_sw128(wgb + kWsOff);
    auto p8_addr = [&]() { return wgb + kPOff + 3 * warp * kPGrp + ln * 16 + (kPL - 128) / 8 * (ln & 24); };
    auto cvt_v = [&]() {
#pragma unroll
      for (int i = 0; i < 26; i++) vf[i] = pack_bf16(acc2[2 * i], acc2[2 * i + 1]);
      asm volatile("and.b32 %0, %2, %3;\nand.b32 %1, %4, %3;\n" : "=r"(z0), "=r"(z1) : "r"(vf[0]), "r"(zero), "r"(vf[1]));
    };
    it++;
    const bool change = !FAST && it == (cta < 2 ? 1 : kSwitch);
    const bool own = !FAST && wg == 0 && it == 0;
    const int stage = own ? 3 : it & 3;
    const uint64_t dE = desc_sw128(kS) + (uint64_t)((stage * kEStage) >> 4);
    if (FAST || it > 0) {
      wg_fence();
      issue_pv(acc1, vf, dP, z0, z1);
      wg_commit();
    }
    mbar_wait(own ? bar_w + 80 : bar_full + 8 * stage, (it >> 2) & 1);
    wg_fence();
    proj(acc2, wQ, dE);
    wg_commit();
    if (wg == 1 && warp == kRefill && ln == 0 && (FAST || it >= 1) && it + kStages - 2 < n_tiles) {
      const int ps = (it - 1) & (kStages - 1);
      if (!FAST && it == 1) load_r(row_of(3), 3, bar_full + 24);
      load_r(it + kStages - 1 < n_tiles ? row_of(it + kStages - 1) : lds(kS + kOpenOff + 4), ps, bar_full + 8 * ps);
    }
    if (wg == 0 && it + 1 == n_tiles && ln == 0) {
      if (warp == kRefill) {
        const int4 c = lds4(kS + kClaimOff);
        uint32_t k;
        asm volatile("atom.global.inc.u32 %0, [%1], %2;\n" : "=r"(k) : "l"((uint64_t)(uint32_t)c.x | ((uint64_t)(uint32_t)c.y << 32)), "r"(c.z) : "memory");
        if (k == 0) sts(kS + kOpenOff, c.w);
      }
      if (warp == 1 && atomicInc(&g_seen, grid - 1) == grid - 1) g_epoch = (unsigned)lds(kS + kOpenOff + 8) / 2;
    }
    if (!FAST && it == 0 && warp == kElect && ln == 0) load_r(((1 + wg) * grid + cta) * kF, 1 + wg, bar_full + 8 * (1 + wg));
    wg_wait<1>();
    fence_acc(acc1);
    store_t<true>(acc1, t_addr + kOOff);
    wg_fence();
    proj(acc1, wK, dE);
    wg_commit();
    wg_wait<1>();
    fence_acc(acc2);
    store_q_t(acc2, t_addr, t_addr + (ln & 16) * 64, q12_addr, ln & 29);
    wg_fence();
    if (FAST) proj_v(acc2, wV, dE); else proj<true>(acc2, wV, dE);
    wg_commit();
    bar_arrive(4 - wg, 256);
    wg_wait<1>();
    fence_acc(acc1);
    store_t<false>(acc1, t_addr + kKOff);
    if (FAST) {
      wg_wait<0>();
      fence_acc(acc2);
      cvt_v();
#pragma unroll
      for (int i = 0; i < 26; i++) asm volatile("" : "+r"(vf[i]));
      sched_barrier();
    }
    publish(wg);
    wg_fence();
    issue_s(acc1, dQ + 512, dK);
    wg_commit();
    if (!FAST) {
      wg_wait<1>();
      fence_acc(acc2);
      cvt_v();
      wg_fence();
    }
    issue_s(acc2, dQ, dK);
    wg_commit();
    if (warp == kElect && ln == 0) {
      if (change) {
        mbar_expect_tx(bar_peek, 16);
        asm volatile("cp.async.bulk.shared::cluster.global.mbarrier::complete_tx::bytes [%0], [%1], 16, [%2];\n" ::"r"(kS + kPeekOff + 16 * wg), "l"(g_state), "r"(bar_peek) : "memory");
      }
      if (FAST || it > 0) tma_out(wg, !FAST && it == 1 ? ((cta & ~1) | wg) * kF : ((it - 1) * grid + cta) * kF);
    }
    wg_wait<1>();
    fence_acc(acc1);
    const float zf = __int_as_float(zero);
    auto q3_dep = [&](const Q3& q, float later) { return ((fmaf(later, zf, q.t) + q.s1) + q.s2) + q.s3; };
    float x[4];
    {
      const bool b0 = ln & 4, b1 = ln & 8, b2 = ln & 16;
#pragma unroll
      for (int h = 0; h < 2; h++) {
        const float* v = acc1 + 2 + h;
        const float x01 = b0 ? v[4] : v[0], x23 = b0 ? v[12] : v[8], x45 = b0 ? v[20] : v[16], x67 = b0 ? v[28] : v[24];
        const float x03 = b1 ? x23 : x01, x47 = b1 ? x67 : x45;
        x[h] = b2 ? x47 : x03;
        const float y01 = b0 ? v[36] : v[32], y23 = b0 ? v[44] : v[40];
        const float y03 = b1 ? y23 : y01;
        x[2 + h] = b2 ? v[48] : y03;
      }
#pragma unroll
      for (int h = 0; h < 4; h++) x[h] = ex2(x[h]);
    }
    float sd = x[0] + x[1];
    if (ln < 18) sd += x[2] + x[3];
    Q3 qd = q3_start(sd, 1);
    float sc;
#pragma unroll
    for (int j = 0; j < 7; j++) set_exp<0>(acc1, j, sc, tail_inv());
    qd = q3_start(q3_dep(qd, sc), 4);
#pragma unroll
    for (int j = 7; j < 12; j++) set_exp<0>(acc1, j, sc, tail_inv());
    sd = q3_dep(qd, sc);
    set_exp<0>(acc1, 12, sc, tail_inv());
    const Q3 qc = q3_start(sc, 1);
    const float sd2 = __shfl_xor_sync(0xffffffffu, sd, 16);
    sched_barrier();
    wg_wait<0>();
    fence_acc(acc2);
    if (change) {
      const int head = wg ^ (cta & 1);
      const unsigned tag = lds(kS + kOpenOff + 8);
      mbar_wait(bar_peek, 0);
      unsigned state = lds(kS + kPeekOff + 16 * wg + 4 * head) - tag;
      for (int n = 0; state > 1 && n < 4096; n++) {
        asm volatile("ld.relaxed.gpu.global.u32 %0, [%1];\n" : "=r"(state) : "l"(g_state + head) : "memory");
        state -= tag;
      }
      int all;
      asm volatile("{.reg .pred p, q;\nsetp.eq.u32 q, %1, 1;\nbar.red.and.pred p, %2, 128, q;\nselp.b32 %0, 1, 0, p;}\n" : "=r"(all) : "r"(state), "n"(1 + wg) : "memory");
      fast = all;
      if (fast) {
        const uint4* src = &g_w[head][0][warp * 32 + ln];
#pragma unroll
        for (int i = 0; i < 13; i++) {
          uint32_t* w = i < 5 ? wQ + 12 + 4 * i : wK + 4 * (i - 5);
          asm volatile("ld.relaxed.gpu.global.v4.u32 {%0,%1,%2,%3}, [%4];\n" : "=r"(w[0]), "=r"(w[1]), "=r"(w[2]), "=r"(w[3]) : "l"(src + i * 128) : "memory");
        }
      }
    }
    float sa, sb;
#pragma unroll
    for (int j = 0; j < kLag; j++) set_exp<0>(acc2, j, sa, tail_inv());
    sc = q3_dep(qc, sa);
    bool bad = out_of_range<FAST>(sc);
    const float ic = rcp(sc);
    {
      sd = fmaf(sa, zf, sd) + sd2;
      bad |= out_of_range<FAST>(sd);
      const float id = rcp(sd);
      stsm_x2(wgb + kPOff + 12 * kPGrp + warp * 16 + ln * kPL, pack_bf16(x[0] * id, x[1] * id), pack_bf16(x[2] * id, x[3] * id));
    }
#pragma unroll
    for (int c = 0; c < 4; c++) norm_set<0>(acc1, c, ic, p8_addr() + 2 * kPGrp);
#pragma unroll
    for (int j = kLag; j < 13; j++) set_exp<0>(acc2, j, sa, tail_inv());
    const Q3 qa = q3_start(sa, 1);
    sched_barrier();
#pragma unroll
    for (int j = 0; j < kLag; j++) set_exp<2>(acc2, j, sb, tail_inv());
    sa = q3_dep(qa, sb);
    bad |= out_of_range<FAST>(sa);
    const float ia = rcp(sa);
#pragma unroll
    for (int c = 0; c < 4; c++) norm_set<0>(acc2, c, ia, p8_addr());
#pragma unroll
    for (int j = kLag; j < kRJ; j++) set_exp<2>(acc2, j, sb, tail_inv());
    PIN(sb);
    sched_barrier();
    if (!FAST && it == 0) mbar_wait(bar_w + 8 * (4 * wg + 3), 0);
    asm volatile("cp.async.bulk.wait_group.read 0;\n" ::: "memory");
    if (wg == 1 || it < n_tiles) bar_sync(3 + wg, 256);
    wg_fence();
    proj_r<FAST, true>(acc1, wV, dE, dW);
    wg_commit();
    sched_barrier();
#pragma unroll
    for (int j = kRJ; j < 13; j++) set_exp<2>(acc2, j, sb, tail_inv());
    sb = q3_end(q3_start(sb, 1));
    bad |= out_of_range<FAST>(sb);
    const float ib = rcp(sb);
#pragma unroll
    for (int c = 0; c < 4; c++) norm_set<2>(acc2, c, ib, p8_addr() + kPGrp);
    asm volatile("{.reg .pred p;\nsetp.ne.u32 p, %1, 0;\n@p st.shared.u8 [%0], %1;}\n" ::"r"(kS + kBadOff + 32 * wg + min(it, 31)), "r"((uint32_t)bad) : "memory");
    wg_wait<0>();
    fence_acc(acc1);
    publish(wg);
    asm volatile("xor.b32 %0, %0, %1;\n" : "+r"(ln) : "r"(zero));
  };
  auto loops = [&](auto wgc) __attribute__((always_inline)) {
    auto won = [&]() { return wgc == 0 && it + 1 < lds(kS + kOpenOff); };
    do iter(wgc, IC<0>()); while (!fast && (it + 1 < n_tiles || won()));
    if (!fast) return;
#pragma unroll
    for (int i = 0; i < 12; i++) wQ[i] = wV[i];
#pragma unroll
    for (int i = 12; i < 32; i++) asm("sub.rn.bf16x2 %0, %0, %1;\n" : "+r"(wV[i]) : "r"(wQ[i]));
#pragma unroll
    for (int s = 0; s < 3; s++) ldsm_x4_t(t_addr + kWsOff + s * 2048, wV[4 * s], wV[4 * s + 1], wV[4 * s + 2], wV[4 * s + 3]);
    do iter(wgc, IC<1>()); while (it + 1 < n_tiles || won());
  };

  auto load_frags = [&](uint32_t (&w)[32], int m) {
    mbar_wait(bar_w + 8 * (4 * wg_r + m), 0);
    const uint32_t a = m < 2 ? t_addr + m * 16384 : t_addr - (kWGBase - kEStage) - (tid >> 7) * (kWGRegion - kEStage);
#pragma unroll
    for (int s = 0; s < 8; s++) ldsm_x4_t(a + s * 2048, w[4 * s], w[4 * s + 1], w[4 * s + 2], w[4 * s + 3]);
  };
  load_frags(wQ, 0);
  scale_wq(wQ);
  load_frags(wK, 1);
  load_frags(wV, 2);
  bar_sync(1 + wg_r, 128);
  if (warp < 2) st_zero(kS + (2 + 2 * wg_r + warp) * kEHalf + kF * 128 + lane * 16);
  if (tid >= 156) {
    const uint8_t* p = p_e + (size_t)(3 * grid + cta) * (kF * kD * 2) + (tid - 156) * 256;
    asm volatile("prefetch.global.L2 [%0];\nprefetch.global.L2 [%0 + 128];\n" ::"l"(p));
  }
  if (wg_r == 1) bar_sync(4, 256);
#pragma unroll
  for (int i = 0; i < 52; i++) asm volatile("" : "=f"(acc1[i]));
#pragma unroll
  for (int i = 0; i < 26; i++) asm volatile("" : "=r"(vf[i]));
  if (wg_r == 0) loops(IC<0>()); else loops(IC<1>());

  int tid2;
  asm volatile("mov.u32 %0, %tid.x;\n" : "=r"(tid2));
  const int wg = __shfl_sync(0xffffffffu, tid2 >> 7, 0);
  wg_fence();
  issue_pv(acc1, vf, desc_p(kS + kWGBase + wg * kWGRegion + kPOff), z0, z1);
  wg_commit();
  if (wg == 0 && it < n_tiles) bar_arrive(4, 256);
  wg_wait<0>();
  fence_acc(acc1);
  store_t<true>(acc1, t_addr + kOOff);
  publish(wg);
  if (warp == kElect && ln == 0) tma_out(wg, it == n_tiles ? lds(kS + kOpenOff + 4) : row_of(it));
  if (tid2 == 64) mbar_wait(bar_full + 8 * (n_tiles & 3), (n_tiles >> 2) & 1);
  __syncthreads();
  if (__any_sync(0xffffffffu, lds16(kS + kBadOff + 2 * ln)))
    exact_redo(&tm_e, &tm_o, &tm_q, &tm_k, &tm_v, it + 1, n_tiles, n_base, n_extra, __ballot_sync(0xffffffffu, smem[kBadOff + 32 * wg + ln]));
  if (warp == kElect && ln == 0) asm volatile("cp.async.bulk.wait_group.read 0;\n" ::: "memory");
}

typedef CUresult (*EncodeFn)(CUtensorMap*, CUtensorMapDataType, cuuint32_t, void*, const cuuint64_t*, const cuuint64_t*,
                             const cuuint32_t*, const cuuint32_t*, CUtensorMapInterleave, CUtensorMapSwizzle,
                             CUtensorMapL2promotion, CUtensorMapFloatOOBfill);

}

extern "C" void kernel_launch(void* const* d_in, const int* in_sizes, int n_in, void* d_out, int out_size) {
  static EncodeFn encode = nullptr;
  static int num_sms = 0;
  if (!encode) {
    void* fn = nullptr;
    cudaDriverEntryPointQueryResult qres;
    cudaGetDriverEntryPoint("cuTensorMapEncodeTiled", &fn, cudaEnableDefault, &qres);
    encode = (EncodeFn)fn;
    int dev = 0;
    cudaGetDevice(&dev);
    cudaDeviceGetAttribute(&num_sms, cudaDevAttrMultiProcessorCount, dev);
    cudaFuncSetAttribute(autoint_kernel, cudaFuncAttributeMaxDynamicSharedMemorySize, kSmemBytes);
  }
  auto make = [&](void* p, uint64_t cols, uint64_t rows, uint32_t box_rows, CUtensorMapL2promotion promo) {
    CUtensorMap tm;
    cuuint64_t dims[2] = {cols, rows};
    cuuint64_t strides[1] = {cols * 2};
    cuuint32_t box[2] = {64, box_rows};
    cuuint32_t estr[2] = {1, 1};
    encode(&tm, CU_TENSOR_MAP_DATA_TYPE_BFLOAT16, 2, p, dims, strides, box, estr, CU_TENSOR_MAP_INTERLEAVE_NONE,
           CU_TENSOR_MAP_SWIZZLE_128B, promo, CU_TENSOR_MAP_FLOAT_OOB_FILL_NONE);
    return tm;
  };
  const CUtensorMap tm_e = make(d_in[0], kD, (uint64_t)kB * kF, kF, CU_TENSOR_MAP_L2_PROMOTION_L2_256B);
  const CUtensorMap tm_o = make(d_out, kD, (uint64_t)kB * kF, kF, CU_TENSOR_MAP_L2_PROMOTION_NONE);
  const CUtensorMap tm_q = make(d_in[1], 64, 256, 128, CU_TENSOR_MAP_L2_PROMOTION_L2_256B);
  const CUtensorMap tm_k = make(d_in[2], 64, 256, 128, CU_TENSOR_MAP_L2_PROMOTION_L2_256B);
  const CUtensorMap tm_v = make(d_in[3], 64, 256, 128, CU_TENSOR_MAP_L2_PROMOTION_L2_256B);
  const CUtensorMap tm_r = make(d_in[4], 128, 128, 128, CU_TENSOR_MAP_L2_PROMOTION_L2_256B);
  const int grid = (num_sms < 2 ? 2 : num_sms < kB / 8 ? num_sms : kB / 8) & ~1;
  const int n_base = kB / grid, rem = kB - n_base * grid, split = 2 * (rem + 2 * kSkip) <= grid;
  autoint_kernel<<<grid, 256, kSmemBytes>>>(tm_e, tm_o, tm_q, tm_k, tm_v, tm_r, (const uint8_t*)d_in[0],
                                             WPtrs{{(const uint8_t*)d_in[1], (const uint8_t*)d_in[2], (const uint8_t*)d_in[3], (const uint8_t*)d_in[4]}},
                                             n_base, split ? 0 : rem, split ? kSkip : 0, 0, split ? rem + 2 * kSkip : 0);
}
```

```cpp
#include <cuda_runtime.h>
#include <cuda_bf16.h>
#include <cuda.h>
#include <stdint.h>

namespace {

constexpr int kB = 4096, kF = 100, kD = 128;
constexpr int kStages = 4;
constexpr int kElect = 3, kRefill = 2;
constexpr int kSwitch = 3;
constexpr int kSkip = 4;
constexpr uint32_t kS = 1024;
constexpr int kEHalf = 104 * 128;
constexpr int kEStage = 2 * kEHalf;
constexpr int kETx = 2 * kF * 128;
constexpr int kOOff = 0;
constexpr int kQOff = 13312;
constexpr int kKOff = kQOff + 16384;
constexpr int kPOff = kQOff;
constexpr int kPL = 144;
constexpr int kPGrp = 13 * kPL;
constexpr int kWsOff = kKOff + 13312;
constexpr int kWGRegion = kWsOff + 16384;
constexpr int kWGBase = kStages * kEStage;
constexpr int kBarOff = kWGBase + 2 * kWGRegion;
constexpr int kOpenOff = kBarOff + 256;
constexpr int kClaimOff = kBarOff + 272;
constexpr int kBadOff = kBarOff + 320;
constexpr int kPeekOff = kBarOff + 384;
constexpr int kTmpOff = kBarOff + 512;
constexpr int kSmemBytes = kTmpOff + 2 * 1024;
static_assert(kWGRegion % 1024 == 0 && kQOff % 1024 == 0 && kKOff % 1024 == 0 && kWsOff % 1024 == 0 && kWGBase % 1024 == 0 &&
              kPOff + 12 * kPGrp + 16 * kPL <= kWsOff && kSmemBytes <= 232448, "smem layout");

__device__ unsigned g_claim[512];
__device__ uint4 g_w[2][13][128];
__device__ __align__(16) unsigned g_state[4];
__device__ unsigned g_seen, g_epoch;

__device__ __forceinline__ uint32_t smem_u32(const void* p) { return (uint32_t)__cvta_generic_to_shared(p); }

__device__ __forceinline__ void wg_fence() { asm volatile("wgmma.fence.sync.aligned;\n" ::: "memory"); }
__device__ __forceinline__ void wg_commit() { asm volatile("wgmma.commit_group.sync.aligned;\n" ::: "memory"); }
template <int N> __device__ __forceinline__ void wg_wait() { asm volatile("wgmma.wait_group.sync.aligned %0;\n" ::"n"(N) : "memory"); }
__device__ __forceinline__ void fence_async() { asm volatile("fence.proxy.async.shared::cta;\n" ::: "memory"); }
__device__ __forceinline__ void bar_sync(int id, int n) { asm volatile("bar.sync %0, %1;\n" ::"r"(id), "r"(n) : "memory"); }
__device__ __forceinline__ void bar_arrive(int id, int n) { asm volatile("bar.arrive %0, %1;\n" ::"r"(id), "r"(n) : "memory"); }

#define ACC_REGS "{%0,%1,%2,%3,%4,%5,%6,%7,%8,%9,%10,%11,%12,%13,%14,%15,%16,%17,%18,%19,%20,%21,%22,%23,%24,%25," \
                 "%26,%27,%28,%29,%30,%31,%32,%33,%34,%35,%36,%37,%38,%39,%40,%41,%42,%43,%44,%45,%46,%47,%48,%49,%50,%51}"
#define ACC_OPS(c, d)                                                                                        \
  c(d[0]), c(d[1]), c(d[2]), c(d[3]), c(d[4]), c(d[5]), c(d[6]), c(d[7]), c(d[8]), c(d[9]), c(d[10]),        \
  c(d[11]), c(d[12]), c(d[13]), c(d[14]), c(d[15]), c(d[16]), c(d[17]), c(d[18]), c(d[19]), c(d[20]),        \
  c(d[21]), c(d[22]), c(d[23]), c(d[24]), c(d[25]), c(d[26]), c(d[27]), c(d[28]), c(d[29]), c(d[30]),        \
  c(d[31]), c(d[32]), c(d[33]), c(d[34]), c(d[35]), c(d[36]), c(d[37]), c(d[38]), c(d[39]), c(d[40]),        \
  c(d[41]), c(d[42]), c(d[43]), c(d[44]), c(d[45]), c(d[46]), c(d[47]), c(d[48]), c(d[49]), c(d[50]), c(d[51])

#define H4(d, i) "+f"(d[i]), "+f"(d[i + 1]), "=f"(d[i + 2]), "=f"(d[i + 3])
#define ACC_HALF(d) H4(d, 0), H4(d, 4), H4(d, 8), H4(d, 12), H4(d, 16), H4(d, 20), H4(d, 24), H4(d, 28), H4(d, 32), H4(d, 36), H4(d, 40), H4(d, 44), H4(d, 48)

__device__ __forceinline__ void fence_acc(float (&d)[52]) {
  asm volatile("" : ACC_OPS("+f", d)::"memory");
}

template <bool ACC>
__device__ __forceinline__ void mma_rs(float (&d)[52], uint32_t a0, uint32_t a1, uint32_t a2, uint32_t a3, uint64_t db) {
  if constexpr (ACC) {
    asm volatile("wgmma.mma_async.sync.aligned.m64n104k16.f32.bf16.bf16 " ACC_REGS
                 ", {%52,%53,%54,%55}, %56, 1, 1, 1, 0;\n"
                 : ACC_OPS("+f", d)
                 : "r"(a0), "r"(a1), "r"(a2), "r"(a3), "l"(db));
  } else {
    asm volatile("wgmma.mma_async.sync.aligned.m64n104k16.f32.bf16.bf16 " ACC_REGS
                 ", {%52,%53,%54,%55}, %56, 0, 1, 1, 0;\n"
                 : ACC_OPS("=f", d)
                 : "r"(a0), "r"(a1), "r"(a2), "r"(a3), "l"(db));
  }
}
__device__ __forceinline__ void mma_ss(float (&d)[52], uint64_t da, uint64_t db) {
  asm volatile("wgmma.mma_async.sync.aligned.m64n104k16.f32.bf16.bf16 " ACC_REGS ", %52, %53, 1, 1, 1, 0, 0;\n"
               : ACC_OPS("+f", d)
               : "l"(da), "l"(db));
}
__device__ __forceinline__ void mma_ss_tied(float (&d)[52], uint64_t da, uint64_t db) {
  asm volatile("wgmma.mma_async.sync.aligned.m64n104k16.f32.bf16.bf16 " ACC_REGS ", %52, %53, 0, 1, 1, 0, 0;\n"
               : ACC_OPS("+f", d)
               : "l"(da), "l"(db));
}
template <bool ACC>
__device__ __forceinline__ void mma_ss_ta(float (&d)[52], uint64_t da, uint64_t db) {
  if constexpr (ACC) {
    asm volatile("wgmma.mma_async.sync.aligned.m64n104k16.f32.bf16.bf16 " ACC_REGS ", %52, %53, 1, 1, 1, 1, 0;\n"
                 : ACC_OPS("+f", d)
                 : "l"(da), "l"(db));
  } else {
    asm volatile("wgmma.mma_async.sync.aligned.m64n104k16.f32.bf16.bf16 " ACC_REGS ", %52, %53, 0, 1, 1, 1, 0;\n"
                 : ACC_OPS("=f", d)
                 : "l"(da), "l"(db));
  }
}

__device__ __forceinline__ void mma_ss_ta_half(float (&d)[52], uint64_t da, uint64_t db) {
  asm volatile("wgmma.mma_async.sync.aligned.m64n104k16.f32.bf16.bf16 " ACC_REGS ", %52, %53, 0, 1, 1, 1, 0;\n"
               : ACC_HALF(d)
               : "l"(da), "l"(db));
}
__device__ __forceinline__ uint64_t desc_sw128(uint32_t saddr) {
  return (uint64_t)((saddr & 0x3FFFF) >> 4) | ((uint64_t)1 << 16) | ((uint64_t)(1024 >> 4) << 32) | ((uint64_t)1 << 62);
}
__device__ __forceinline__ uint64_t desc_p(uint32_t saddr) {
  return (uint64_t)((saddr & 0x3FFFF) >> 4) | ((uint64_t)(kPL >> 4) << 16) | ((uint64_t)(kPGrp >> 4) << 32);
}

__device__ __forceinline__ uint32_t pack_bf16(float lo, float hi) {
  uint32_t r;
  asm("cvt.rn.bf16x2.f32 %0, %1, %2;\n" : "=r"(r) : "f"(hi), "f"(lo));
  return r;
}
__device__ __forceinline__ uint32_t pack_bf16_relu(float lo, float hi) {
  uint32_t r;
  asm("cvt.rn.relu.bf16x2.f32 %0, %1, %2;\n" : "=r"(r) : "f"(hi), "f"(lo));
  return r;
}
__device__ __forceinline__ float ex2(float x) {
  float y;
  asm("ex2.approx.ftz.f32 %0, %1;\n" : "=f"(y) : "f"(x));
  return y;
}
__device__ __forceinline__ float rcp(float x) {
  float y;
  asm("rcp.approx.ftz.f32 %0, %1;\n" : "=f"(y) : "f"(x));
  return y;
}
__device__ __forceinline__ float rsq(float x) {
  float y;
  asm("rsqrt.approx.ftz.f32 %0, %1;\n" : "=f"(y) : "f"(x));
  return y;
}
__device__ __forceinline__ void stsm_x4(uint32_t addr, uint32_t r0, uint32_t r1, uint32_t r2, uint32_t r3) {
  asm volatile("stmatrix.sync.aligned.m8n8.x4.shared.b16 [%0], {%1,%2,%3,%4};\n" ::"r"(addr), "r"(r0), "r"(r1), "r"(r2), "r"(r3) : "memory");
}
__device__ __forceinline__ void stsm_x2(uint32_t addr, uint32_t r0, uint32_t r1) {
  asm volatile("stmatrix.sync.aligned.m8n8.x2.shared.b16 [%0], {%1,%2};\n" ::"r"(addr), "r"(r0), "r"(r1) : "memory");
}
__device__ __forceinline__ void stsm_x1(uint32_t addr, uint32_t r0) {
  asm volatile("stmatrix.sync.aligned.m8n8.x1.shared.b16 [%0], {%1};\n" ::"r"(addr), "r"(r0) : "memory");
}
__device__ __forceinline__ void stsm_x4_t(uint32_t addr, uint32_t r0, uint32_t r1, uint32_t r2, uint32_t r3) {
  asm volatile("stmatrix.sync.aligned.m8n8.x4.trans.shared.b16 [%0], {%1,%2,%3,%4};\n" ::"r"(addr), "r"(r0), "r"(r1), "r"(r2), "r"(r3) : "memory");
}
__device__ __forceinline__ void stsm_x2_t(uint32_t addr, uint32_t r0, uint32_t r1) {
  asm volatile("stmatrix.sync.aligned.m8n8.x2.trans.shared.b16 [%0], {%1,%2};\n" ::"r"(addr), "r"(r0), "r"(r1) : "memory");
}
__device__ __forceinline__ void ldsm_x4_t(uint32_t addr, uint32_t& r0, uint32_t& r1, uint32_t& r2, uint32_t& r3) {
  asm volatile("ldmatrix.sync.aligned.m8n8.x4.trans.shared.b16 {%0,%1,%2,%3}, [%4];\n" : "=r"(r0), "=r"(r1), "=r"(r2), "=r"(r3) : "r"(addr) : "memory");
}
__device__ __forceinline__ int lds16(uint32_t addr) {
  uint16_t v;
  asm volatile("ld.shared.u16 %0, [%1];\n" : "=h"(v) : "r"(addr) : "memory");
  return v;
}
__device__ __forceinline__ int lds(uint32_t addr) {
  int v;
  asm volatile("ld.shared.u32 %0, [%1];\n" : "=r"(v) : "r"(addr) : "memory");
  return v;
}
__device__ __forceinline__ int4 lds4(uint32_t addr) {
  int4 v;
  asm volatile("ld.shared.v4.u32 {%0,%1,%2,%3}, [%4];\n" : "=r"(v.x), "=r"(v.y), "=r"(v.z), "=r"(v.w) : "r"(addr) : "memory");
  return v;
}
__device__ __forceinline__ void sts(uint32_t addr, int v) { asm volatile("st.shared.u32 [%0], %1;\n" ::"r"(addr), "r"(v) : "memory"); }
__device__ __forceinline__ void sts4(uint32_t addr, int x, int y, int z, int w) {
  asm volatile("st.shared.v4.u32 [%0], {%1,%2,%3,%4};\n" ::"r"(addr), "r"(x), "r"(y), "r"(z), "r"(w) : "memory");
}
__device__ __forceinline__ void mbar_init(uint32_t bar, int count) {
  asm volatile("mbarrier.init.shared::cta.b64 [%0], %1;\n" ::"r"(bar), "r"(count) : "memory");
}
__device__ __forceinline__ void mbar_expect_tx(uint32_t bar, int bytes) {
  asm volatile("mbarrier.arrive.expect_tx.shared::cta.b64 _, [%0], %1;\n" ::"r"(bar), "r"(bytes) : "memory");
}
__device__ __forceinline__ void mbar_wait(uint32_t bar, uint32_t parity) {
  asm volatile(
      "{\n.reg .pred p;\n"
      "WAIT_%=:\n"
      "mbarrier.try_wait.parity.shared::cta.b64 p, [%0], %1;\n"
      "@p bra DONE_%=;\n"
      "bra WAIT_%=;\n"
      "DONE_%=:\n}\n" ::"r"(bar), "r"(parity) : "memory");
}
__device__ __forceinline__ void tma_load_2d(uint32_t dst, const CUtensorMap* tm, int c0, int c1, uint32_t bar) {
  asm volatile("cp.async.bulk.tensor.2d.shared::cluster.global.mbarrier::complete_tx::bytes [%0], [%1, {%3, %4}], [%2];\n" ::"r"(dst),
               "l"(tm), "r"(bar), "r"(c0), "r"(c1) : "memory");
}
__device__ __forceinline__ void tma_store_2d(const CUtensorMap* tm, uint32_t src, int c0, int c1) {
  asm volatile("cp.async.bulk.tensor.2d.global.shared::cta.bulk_group [%0, {%2, %3}], [%1];\n" ::"l"(tm), "r"(src), "r"(c0), "r"(c1) : "memory");
}

__device__ __forceinline__ void mma_rs_tied(float (&d)[52], uint32_t a0, uint32_t a1, uint32_t a2, uint32_t a3, uint64_t db) {
  asm volatile("wgmma.mma_async.sync.aligned.m64n104k16.f32.bf16.bf16 " ACC_REGS ", {%52,%53,%54,%55}, %56, 0, 1, 1, 0;\n"
               : ACC_OPS("+f", d)
               : "r"(a0), "r"(a1), "r"(a2), "r"(a3), "l"(db));
}
template <bool TIED = false>
__device__ __forceinline__ void proj(float (&acc)[52], const uint32_t (&w)[32], uint64_t de) {
#pragma unroll
  for (int s = 0; s < 8; s++) {
    uint64_t db = de + (uint64_t)(((s >> 2) * kEHalf + (s & 3) * 32) >> 4);
    if (s == 0) { if (TIED) mma_rs_tied(acc, w[0], w[1], w[2], w[3], db); else mma_rs<false>(acc, w[0], w[1], w[2], w[3], db); }
    else mma_rs<true>(acc, w[4 * s], w[4 * s + 1], w[4 * s + 2], w[4 * s + 3], db);
  }
}
__device__ __forceinline__ void proj_v(float (&acc)[52], const uint32_t (&w)[32], uint64_t de) {
#pragma unroll
  for (int s = 3; s < 8; s++) {
    uint64_t db = de + (uint64_t)(((s >> 2) * kEHalf + (s & 3) * 32) >> 4);
    mma_rs<true>(acc, w[4 * s], w[4 * s + 1], w[4 * s + 2], w[4 * s + 3], db);
  }
}
__device__ __forceinline__ void mma_rs_half(float (&d)[52], uint32_t a0, uint32_t a1, uint32_t a2, uint32_t a3, uint64_t db) {
  asm volatile("wgmma.mma_async.sync.aligned.m64n104k16.f32.bf16.bf16 " ACC_REGS ", {%52,%53,%54,%55}, %56, 0, 1, 1, 0;\n"
               : ACC_HALF(d)
               : "r"(a0), "r"(a1), "r"(a2), "r"(a3), "l"(db));
}
template <bool REGS, bool HALF>
__device__ __forceinline__ void proj_r(float (&acc)[52], const uint32_t* w, uint64_t de, uint64_t dw) {
#pragma unroll
  for (int s = 0; s < 8; s++) {
    uint64_t db = de + (uint64_t)(((s >> 2) * kEHalf + (s & 3) * 32) >> 4);
    if (REGS && s == 0) mma_rs_half(acc, w[0], w[1], w[2], w[3], db);
    else if (REGS && s < 3) mma_rs<true>(acc, w[4 * s], w[4 * s + 1], w[4 * s + 2], w[4 * s + 3], db);
    else if (s == 0) { if (HALF) mma_ss_ta_half(acc, dw, db); else mma_ss_ta<false>(acc, dw, db); }
    else mma_ss_ta<true>(acc, dw + (uint64_t)(s * 128), db);
  }
}

template <bool RELU>
__device__ __forceinline__ void store_t(const float (&a)[52], uint32_t addr) {
  auto pk = [&](int i) { return RELU ? pack_bf16_relu(a[i], a[i + 1]) : pack_bf16(a[i], a[i + 1]); };
#pragma unroll
  for (int j = 0; j < 12; j += 2) stsm_x4_t(addr + j * 1024, pk(4 * j), pk(4 * j + 2), pk(4 * j + 4), pk(4 * j + 6));
  stsm_x2_t(addr + 12 * 1024, pk(48), pk(50));
}
__device__ __forceinline__ void store_q_t(const float (&a)[52], uint32_t addr, uint32_t addr_hi, uint32_t addr_last, int src) {
  auto pk = [&](int i) { return pack_bf16(a[i], a[i + 1]); };
#pragma unroll
  for (int w = 0; w < 4; w++) {
    stsm_x4_t(addr + kQOff + 2 * w * 1024, pk(12 * w), pk(12 * w + 2), pk(12 * w + 4), pk(12 * w + 6));
    if (w & 1) stsm_x4_t(addr_hi + kQOff + (6 + 2 * w) * 1024, pk(12 * w - 4), pk(12 * w - 2), pk(12 * w + 8), pk(12 * w + 10));
  }
  const uint32_t r0 = __shfl_sync(0xffffffffu, pk(48), src), r1 = __shfl_sync(0xffffffffu, pk(50), src);
  stsm_x4_t(addr_last, r0, r1, r0, r1);
  stsm_x4_t(addr_last ^ 0x240, r0, r1, r0, r1);
}

constexpr float kC = 0.125f * 1.4426950408889634f;

__device__ __forceinline__ float quad_sum(float t) {
  t += __shfl_xor_sync(0xffffffffu, t, 1);
  t += __shfl_xor_sync(0xffffffffu, t, 2);
  return t;
}
#define PIN(x) asm volatile("" : "+f"(x)::"memory")
struct Q3 { float t, s1, s2, s3; };
__device__ __forceinline__ Q3 q3_start(float t, int m) {
  Q3 q;
  q.t = t;
  q.s1 = __shfl_xor_sync(0xffffffffu, t, m);
  q.s2 = __shfl_xor_sync(0xffffffffu, t, 2 * m);
  q.s3 = __shfl_xor_sync(0xffffffffu, t, 3 * m);
  return q;
}
__device__ __forceinline__ float q3_end(const Q3& q) { return (q.t + q.s1) + (q.s2 + q.s3); }
template <bool TIGHT> __device__ __forceinline__ bool out_of_range(float t) {
  return TIGHT ? !(t >= 0x1p-7f && t <= 0x1p12f) : !(t >= 0x1p-30f && t <= 0x1p30f);
}

template <int O> __device__ __forceinline__ void set_exp(float (&s)[52], int j, float& t, bool tail_invalid) {
  s[4 * j + O] = ex2(s[4 * j + O]);
  s[4 * j + O + 1] = ex2(s[4 * j + O + 1]);
  if (j == 0) t = s[O] + s[O + 1];
  else if (j < 12 || !tail_invalid) { t += s[4 * j + O]; t += s[4 * j + O + 1]; }
}
template <int O> __device__ __forceinline__ void norm_set(const float (&s)[52], int c, float iv, uint32_t paddr) {
  const int i = 16 * c + O;
  if (c < 3) stsm_x4(paddr + 4 * c * kPL, pack_bf16(s[i] * iv, s[i + 1] * iv), pack_bf16(s[i + 4] * iv, s[i + 5] * iv),
                     pack_bf16(s[i + 8] * iv, s[i + 9] * iv), pack_bf16(s[i + 12] * iv, s[i + 13] * iv));
  else stsm_x1(paddr + 12 * kPL, pack_bf16(s[48 + O] * iv, s[49 + O] * iv));
}
template <int O> __device__ __forceinline__ void set_exact(float (&s)[52], uint32_t paddr, bool tail_invalid) {
  if (tail_invalid) { s[48 + O] = -INFINITY; s[49 + O] = -INFINITY; }
  float m = fmaxf(s[O], s[O + 1]);
#pragma unroll
  for (int j = 1; j < 13; j++) m = fmaxf(m, fmaxf(s[4 * j + O], s[4 * j + O + 1]));
  m = fmaxf(m, __shfl_xor_sync(0xffffffffu, m, 1));
  m = fmaxf(m, __shfl_xor_sync(0xffffffffu, m, 2));
  float t;
#pragma unroll
  for (int j = 0; j < 13; j++) {
    s[4 * j + O] -= m; s[4 * j + O + 1] -= m;
    set_exp<O>(s, j, t, tail_invalid);
  }
  const float iv = rcp(quad_sum(t));
#pragma unroll
  for (int c = 0; c < 4; c++) norm_set<O>(s, c, iv, paddr);
}

__device__ __forceinline__ void sched_barrier() { asm volatile("pmevent 1;\n" ::: "memory"); }

__device__ __forceinline__ void scale_wq(uint32_t (&w)[32]) {
#pragma unroll
  for (int i = 0; i < 32; i++)
    asm("{.reg .b32 t;\nmul.rn.bf16x2 t, %0, %2;\nfma.rn.bf16x2 %0, %0, %1, t;}\n" : "+r"(w[i]) : "r"(0x3e393e39u), "r"(0xb9acb9acu));
}
__device__ __forceinline__ void issue_s(float (&a)[52], uint64_t dq, uint64_t dk) {
#pragma unroll
  for (int s = 0; s < 4; s++) {
    if (s == 0) mma_ss_tied(a, dq, dk);
    else mma_ss(a, dq + 2 * s, dk + 2 * s);
  }
}
__device__ __forceinline__ void issue_pv(float (&a)[52], const uint32_t (&vf)[26], uint64_t dp, uint32_t z0 = 0, uint32_t z1 = 0) {
#pragma unroll
  for (int s = 0; s < 6; s++) mma_rs<true>(a, vf[4 * s], vf[4 * s + 1], vf[4 * s + 2], vf[4 * s + 3], dp + (kPL / 8) * s);
  mma_rs<true>(a, vf[24], vf[25], z0, z1, (dp + (kPL / 8) * 6) & ~((uint64_t)0x3FFF << 16));
}

__device__ __forceinline__ void exact_redo(const CUtensorMap* tm_e, const CUtensorMap* tm_o, const CUtensorMap* tm_q,
                                        const CUtensorMap* tm_k, const CUtensorMap* tm_v, int n_tiles) {
  constexpr uint32_t sbase = kS;
  auto zero = [&]() {
    uint32_t z;
    asm volatile("ld.volatile.shared.u32 %0, [%1];\n" : "=r"(z) : "r"(sbase + kF * 128) : "memory");
    return z;
  };
  const int tid = threadIdx.x + zero(), wg = tid >> 7, warp = (tid >> 5) & 3, lane = tid & 31;
  const int grid = gridDim.x - 2, cta = blockIdx.x - 2, head = wg ^ (cta & 1);
  const uint32_t wgb = sbase + kWGBase + wg * kWGRegion;
  const uint32_t bar_w = sbase + kBarOff + 64 + 32 * wg, bar_e = sbase + kBarOff + 128 + 8 * wg;
  const uint32_t flags = __ballot_sync(0xffffffffu, lds16(sbase + kBadOff + 32 * wg + (lane & ~1)) >> (8 * (lane & 1)) & 255);
  const int n_iter = wg == 0 ? max(n_tiles, lds(sbase + kOpenOff)) : n_tiles;
  const bool elected = warp == kElect && lane == 0;
  const bool tail_invalid = (lane & 2) != 0;
  const uint32_t t_addr = wgb + ((lane >> 4) * 8 + (lane & 7)) * 128 + (((2 * warp + ((lane >> 3) & 1)) ^ (lane & 7)) << 4);
  const uint32_t q12_k = (2 * (lane >> 4) + ((lane >> 2) & 1) + 2 * (lane & 3)) & 7;
  uint32_t q12_addr = wgb + kQOff + (9 + 2 * (lane & 3)) * 1024 + q12_k * 128 + (((2 * warp + ((lane >> 3) & 1)) ^ q12_k) << 4);
  const uint32_t p8_addr = wgb + kPOff + lane * 16 + (kPL - 128) / 8 * (lane & 24);
  auto e_desc = [&](int st) { return desc_sw128(sbase + (st + wg + zero()) * kEStage); };
  auto g_addr = [&]() { return wgb + zero(); };

  if (elected) {
    asm volatile("cp.async.bulk.wait_group 0;\n" ::: "memory");
    mbar_expect_tx(bar_w, 3 * 16384);
    tma_load_2d(wgb, tm_q, 0, head * 128, bar_w);
    tma_load_2d(wgb + 16384, tm_k, 0, head * 128, bar_w);
    tma_load_2d(sbase + (2 + wg) * kEStage, tm_v, 0, head * 128, bar_w);
  }
  mbar_wait(bar_w, 1);
  uint32_t wQ[32], wK[32], vf[26];
#pragma unroll
  for (int s = 0; s < 8; s++) {
    ldsm_x4_t(t_addr + s * 2048, wQ[4 * s], wQ[4 * s + 1], wQ[4 * s + 2], wQ[4 * s + 3]);
    ldsm_x4_t(t_addr + 16384 + s * 2048, wK[4 * s], wK[4 * s + 1], wK[4 * s + 2], wK[4 * s + 3]);
  }
  scale_wq(wQ);
  auto publish = [&]() {
    bar_sync(1 + wg, 128);
    fence_async();
  };
  bar_sync(1 + wg, 128);
  float acc1[52], acc2[52];
  uint32_t ph = 0;
  for (int t = 0; t < n_iter; t++) {
    if (!__any_sync(0xffffffffu, (flags >> min(t, 31)) & 1)) continue;
    const int row = t == n_tiles ? lds(sbase + kOpenOff + 4) : (t * grid + (t == 0 ? cta ^ head : cta)) * kF;
    if (elected) {
      mbar_expect_tx(bar_e, kETx);
      tma_load_2d(sbase + wg * kEStage, tm_e, 0, row, bar_e);
      tma_load_2d(sbase + wg * kEStage + kEHalf, tm_e, 64, row, bar_e);
    }
    mbar_wait(bar_e, ph);
    ph ^= 1;
    {
      const uint64_t dE = e_desc(0);
      wg_fence();
      proj(acc2, wQ, dE);
      proj(acc1, wK, dE);
      wg_commit();
    }
    wg_wait<0>();
    fence_acc(acc1);
    fence_acc(acc2);
    store_q_t(acc2, t_addr, t_addr + (lane >> 4) * 1024, q12_addr, lane & 29);
    store_t<false>(acc1, t_addr + kKOff);
    {
      const uint64_t dE = e_desc(0), dWv = e_desc(2);
      wg_fence();
      proj_r<false, false>(acc2, nullptr, dE, dWv);
      wg_commit();
    }
    wg_wait<0>();
    fence_acc(acc2);
#pragma unroll
    for (int i = 0; i < 26; i++) vf[i] = pack_bf16(acc2[2 * i], acc2[2 * i + 1]);
    publish();
    {
      const uint32_t g = g_addr();
      const uint64_t dQ = desc_sw128(g + kQOff), dK = desc_sw128(g + kKOff);
      wg_fence();
      issue_s(acc1, dQ, dK);
      issue_s(acc2, dQ + 512, dK);
      wg_commit();
    }
    wg_wait<0>();
    fence_acc(acc1);
    fence_acc(acc2);
    bar_sync(1 + wg, 128);
    set_exact<0>(acc1, p8_addr + 3 * warp * kPGrp, tail_invalid);
    set_exact<2>(acc1, p8_addr + (3 * warp + 1) * kPGrp, tail_invalid);
    set_exact<0>(acc2, p8_addr + (3 * warp + 2) * kPGrp, tail_invalid);
    set_exact<2>(acc2, wgb + kPOff + 12 * kPGrp + (lane >> 3) * kPL + warp * 16, tail_invalid);
    publish();
    {
      const uint32_t g = g_addr();
      const uint64_t dE = e_desc(0), dW = desc_sw128(g + kWsOff), dP = desc_p(g + kPOff);
      wg_fence();
      proj_r<false, false>(acc1, nullptr, dE, dW);
      issue_pv(acc1, vf, dP);
      wg_commit();
    }
    wg_wait<0>();
    fence_acc(acc1);
    store_t<true>(acc1, t_addr + kOOff);
    publish();
    if (elected) {
      tma_store_2d(tm_o, wgb + kOOff, head * 64, row);
      asm volatile("cp.async.bulk.commit_group;\n" ::: "memory");
      asm volatile("cp.async.bulk.wait_group 0;\n" ::: "memory");
    }
    bar_sync(1 + wg, 128);
  }
}

#define D32_REGS "{%0,%1,%2,%3,%4,%5,%6,%7,%8,%9,%10,%11,%12,%13,%14,%15,%16,%17,%18,%19,%20,%21,%22,%23,%24,%25,%26,%27,%28,%29,%30,%31}"
#define D32_OPS(c, d)                                                                                        \
  c(d[0]), c(d[1]), c(d[2]), c(d[3]), c(d[4]), c(d[5]), c(d[6]), c(d[7]), c(d[8]), c(d[9]), c(d[10]),        \
  c(d[11]), c(d[12]), c(d[13]), c(d[14]), c(d[15]), c(d[16]), c(d[17]), c(d[18]), c(d[19]), c(d[20]),        \
  c(d[21]), c(d[22]), c(d[23]), c(d[24]), c(d[25]), c(d[26]), c(d[27]), c(d[28]), c(d[29]), c(d[30]), c(d[31])
template <int ACC, int SA, int T>
__device__ __forceinline__ void mma64_ss(float (&d)[32], uint64_t da, uint64_t db) {
  if constexpr (ACC)
    asm volatile("wgmma.mma_async.sync.aligned.m64n64k16.f32.bf16.bf16 " D32_REGS ", %32, %33, 1, %34, 1, %35, %35;\n"
                 : D32_OPS("+f", d) : "l"(da), "l"(db), "n"(SA), "n"(T));
  else
    asm volatile("wgmma.mma_async.sync.aligned.m64n64k16.f32.bf16.bf16 " D32_REGS ", %32, %33, 0, %34, 1, %35, %35;\n"
                 : D32_OPS("=f", d) : "l"(da), "l"(db), "n"(SA), "n"(T));
}
template <int ACC, int T>
__device__ __forceinline__ void mma64_rs(float (&d)[32], const uint32_t* a, uint64_t db) {
  if constexpr (ACC)
    asm volatile("wgmma.mma_async.sync.aligned.m64n64k16.f32.bf16.bf16 " D32_REGS ", {%32,%33,%34,%35}, %36, 1, 1, 1, %37;\n"
                 : D32_OPS("+f", d) : "r"(a[0]), "r"(a[1]), "r"(a[2]), "r"(a[3]), "l"(db), "n"(T));
  else
    asm volatile("wgmma.mma_async.sync.aligned.m64n64k16.f32.bf16.bf16 " D32_REGS ", {%32,%33,%34,%35}, %36, 0, 1, 1, %37;\n"
                 : D32_OPS("=f", d) : "r"(a[0]), "r"(a[1]), "r"(a[2]), "r"(a[3]), "l"(db), "n"(T));
}
__device__ __forceinline__ void mma64_done(float (&d)[32]) {
  wg_commit();
  wg_wait<0>();
  asm volatile("" : D32_OPS("+f", d)::"memory");
}
__device__ __forceinline__ float bf_lo(uint32_t x) { return __uint_as_float(x << 16); }
__device__ __forceinline__ float bf_hi(uint32_t x) { return __uint_as_float(x & 0xffff0000u); }
__device__ __forceinline__ void split2(float x, float y, uint32_t& hi, uint32_t& lo) {
  hi = pack_bf16(x, y);
  lo = pack_bf16(x - bf_lo(hi), y - bf_hi(hi));
}
__device__ __forceinline__ float ldsf(uint32_t a) { return __int_as_float(lds(a)); }
__device__ __forceinline__ float2 ldsf2(uint32_t a) {
  float2 v;
  asm volatile("ld.shared.v2.f32 {%0,%1}, [%2];\n" : "=f"(v.x), "=f"(v.y) : "r"(a) : "memory");
  return v;
}
__device__ __forceinline__ float4 ldsf4(uint32_t a) {
  float4 v;
  asm volatile("ld.shared.v4.f32 {%0,%1,%2,%3}, [%4];\n" : "=f"(v.x), "=f"(v.y), "=f"(v.z), "=f"(v.w) : "r"(a) : "memory");
  return v;
}
__device__ __forceinline__ void stsf2(uint32_t a, float x, float y) { asm volatile("st.shared.v2.f32 [%0], {%1,%2};\n" ::"r"(a), "f"(x), "f"(y) : "memory"); }
__device__ __forceinline__ void stsf4(uint32_t a, float x, float y, float z, float w) {
  asm volatile("st.shared.v4.f32 [%0], {%1,%2,%3,%4};\n" ::"r"(a), "f"(x), "f"(y), "f"(z), "f"(w) : "memory");
}
__device__ __forceinline__ float tf_lo(float x) { return x - __uint_as_float(__float_as_uint(x) & 0xffffe000u); }
__device__ __forceinline__ void mma_tf32(float* c, float a0, float a1, float a2, float a3, float b0, float b1) {
  asm("mma.sync.aligned.m16n8k8.row.col.f32.tf32.tf32.f32 {%0,%1,%2,%3}, {%4,%5,%6,%7}, {%8,%9}, {%0,%1,%2,%3};\n"
      : "+f"(c[0]), "+f"(c[1]), "+f"(c[2]), "+f"(c[3])
      : "r"(__float_as_uint(a0)), "r"(__float_as_uint(a1)), "r"(__float_as_uint(a2)), "r"(__float_as_uint(a3)), "r"(__float_as_uint(b0)), "r"(__float_as_uint(b1)));
}
__device__ __forceinline__ float warp_sum(float t) {
#pragma unroll
  for (int m = 1; m < 32; m *= 2) t += __shfl_xor_sync(0xffffffffu, t, m);
  return t;
}

__device__ __forceinline__ void transform_weights(int z, int warp) {
  unsigned epoch = 0;
  if (threadIdx.x == 192) epoch = *(volatile unsigned*)&g_epoch;
  const int t = threadIdx.x & 127, lane = t & 31, q = lane & 3, r = 16 * warp + (lane >> 2);
  constexpr uint32_t kWq = kS + kWGBase, kWk = kWq + 16384, kWv = kS + kEStage;
  auto tile_hi = [](int s) { return kS + kWGBase + s * kWGRegion + 32768; };
  auto tile_lo = [](int s) { return kS + (1 + s) * kEStage + 16384; };
  const uint32_t tX = z ? kWv : kWq, tH = tile_hi(z), tL = tile_lo(z);
  const uint32_t big = kS + kWGBase + kWGRegion + z * 16384, gt = kS + z * kEHalf;
  const uint32_t n2 = kS + kTmpOff + z * 1024, buf = kS + 2 * kEStage + z * 8192;
  uint4* dst = &g_w[blockIdx.x][0][t] + (8 * z - 3) * 128;
  auto store_big = [&](const float (&d)[32]) {
#pragma unroll
    for (int g = 0; g < 8; g++) {
      const uint32_t a = big + r * 256 + ((g ^ (lane >> 2)) << 5) + 8 * q;
      stsf2(a, d[4 * g], d[4 * g + 1]);
      stsf2(a + 2048, d[4 * g + 2], d[4 * g + 3]);
    }
  };
#pragma unroll 1
  for (int i = 0; i < 5; i++) sts4(gt + 16 * t + 2048 * i, 0, 0, 0, 0);
  mbar_wait(kS + kBarOff + 64 + 16 * z, 0);
  float d[32];
  wg_fence();
#pragma unroll
  for (int s = 0; s < 4; s++) {
    if (s == 0) mma64_ss<0, 1, 0>(d, desc_sw128(tX - 2048 * z), desc_sw128(tX));
    else mma64_ss<1, 1, 0>(d, desc_sw128(tX - 2048 * z) + 2 * s, desc_sw128(tX) + 2 * s);
  }
  mma64_done(d);
  bool ok = true;
  uint32_t fh[16], fl[16];
  auto split_d = [&](int n) {
#pragma unroll
    for (int i = 0; i < n; i++) split2(d[2 * i], d[2 * i + 1], fh[i], fl[i]);
  };
  const int wr = warp - z, c8 = lane >> 2;
  if ((unsigned)wr < 3) {
    const bool dg = c8 >> 1 == q, odd = c8 & 1;
    if (dg) {
      const float x0 = odd ? d[1] : d[0], x1 = odd ? d[9] : d[8], x2 = odd ? d[17] : d[16];
      const float y0 = odd ? d[7] : d[6], y1 = odd ? d[15] : d[14], y2 = odd ? d[23] : d[22];
      sts(n2 + 512 + 64 * wr + 4 * c8, __float_as_int(rsq(wr == 0 ? x0 : wr == 1 ? x1 : x2)));
      sts(n2 + 544 + 64 * wr + 4 * c8, __float_as_int(rsq(wr == 0 ? y0 : wr == 1 ? y1 : y2)));
    }
    bar_sync(8 + z, 96);
    const float r0 = ldsf(n2 + 512 + 64 * wr + 4 * c8), r1 = ldsf(n2 + 544 + 64 * wr + 4 * c8);
    auto scale = [&](float a, float b) {
#pragma unroll
      for (int g = 0; g < 6; g++) {
        const float2 c = ldsf2(n2 + 512 + 32 * g + 8 * q);
        d[4 * g] *= a * c.x; d[4 * g + 1] *= a * c.y; d[4 * g + 2] *= b * c.x; d[4 * g + 3] *= b * c.y;
      }
    };
    scale(r0, r1);
    const float fe = dg && !odd, fo = dg && odd;
    const uint32_t lo_mask = q < 2 ? 0u : 0xffffe000u;
    const bool e = q & 1;
#pragma unroll 1
    for (int k = 0; k < 3; k++) {
      float x[8], m[8];
      const float ge = wr == k ? fe : 0.f, go = wr == k ? fo : 0.f;
#pragma unroll
      for (int i = 0; i < 8; i++) m[i] = d[i];
      d[0] -= ge; d[1] -= go; d[6] -= ge; d[7] -= go;
      const uint32_t xb = buf + 4096 * (k & 1) + 1024 * (wr - k < 0 ? wr - k + 3 : wr - k) + 16 * lane;
      stsf4(xb, d[0], d[1], d[4], d[5]);
      stsf4(xb + 512, d[2], d[3], d[6], d[7]);
#pragma unroll
      for (int i = 0; i < 8; i++) x[i] = d[i];
      d[0] -= ge; d[1] -= go; d[6] -= ge; d[7] -= go;
      if (wr == k) {
#pragma unroll
        for (int h = 0; h < 2; h++) {
#pragma unroll 1
          for (int p = 0; p < 4; p++) {
            const float ie = q == p ? fe : 0.f, io = q == p ? fo : 0.f;
            const float px = __shfl_sync(0xffffffffu, m[6 * h], 9 * p), py = __shfl_sync(0xffffffffu, m[6 * h + 1], 9 * p);
            const float pw = __shfl_sync(0xffffffffu, m[6 * h + 1], 9 * p + 4);
            m[6 * h] -= ie; m[6 * h + 1] -= io;
            float y[4];
#pragma unroll
            for (int i = 0; i < 4; i++) y[i] = __shfl_sync(0xffffffffu, m[4 * h + i], p, 4);
            m[6 * h] -= ie; m[6 * h + 1] -= io;
            const float id = rcp(px * pw - py * py), po = e ? px : pw;
            const float o0 = e ? y[1] : y[0], s0 = e ? y[0] : y[1], o1 = e ? y[3] : y[2], s1 = e ? y[2] : y[3];
            const float w0 = (s0 * py - o0 * po) * id, w1 = (s1 * py - o1 * po) * id;
            const float b0 = o0 - __uint_as_float(__float_as_uint(o0) & lo_mask), b1 = o1 - __uint_as_float(__float_as_uint(o1) & lo_mask);
            mma_tf32(m, w0, w1, tf_lo(w0), tf_lo(w1), b0, b0);
            mma_tf32(m + 4, w0, w1, tf_lo(w0), tf_lo(w1), b1, b1);
          }
        }
        stsf4(buf + 4096 * (k & 1) + 3072 + 16 * lane, m[0], m[1], m[4], m[5]);
        stsf4(buf + 4096 * (k & 1) + 3584 + 16 * lane, m[2], m[3], m[6], m[7]);
      }
      bar_sync(8 + z, 96);
      auto mul = [&](auto c0, auto c1, int n, const float (&a)[8], const float4* b) {
        float l[8];
#pragma unroll
        for (int i = 0; i < 8; i++) l[i] = tf_lo(a[i]);
#pragma unroll
        for (int t = 0; t < 3; t++) {
          const float* u = t == 1 ? l : a;
#pragma unroll
          for (int j = 0; j < n; j++) mma_tf32(c0(j), u[0], u[2], u[1], u[3], t == 2 ? tf_lo(b[j].x) : b[j].x, t == 2 ? tf_lo(b[j].y) : b[j].y);
#pragma unroll
          for (int j = 0; j < n; j++) mma_tf32(c1(j), u[4], u[6], u[5], u[7], t == 2 ? tf_lo(b[j].z) : b[j].z, t == 2 ? tf_lo(b[j].w) : b[j].w);
        }
      };
      float4 b[8];
#pragma unroll
      for (int j = 0; j < 8; j++) b[(j + 6) % 8] = ldsf4(buf + 4096 * (k & 1) + 512 * ((j + 6) % 8) + 16 * lane);
      float m2[8];
#pragma unroll
      for (int i = 0; i < 8; i++) m[i] = m2[i] = 0.f;
      mul([&](int j) { return m + 4 * j; }, [&](int j) { return m2 + 4 * j; }, 2, x, b + 6);
#pragma unroll
      for (int i = 0; i < 8; i++) m[i] += m2[i];
      mul([&](int j) { return d + 4 * j; }, [&](int j) { return d + 4 * j; }, 6, m, b);
#pragma unroll
      for (int i = 0; i < 8; i++) { const float v = d[i]; d[i] = d[8 + i]; d[8 + i] = d[16 + i]; d[16 + i] = v; }
    }
#pragma unroll
    for (int i = 0; i < 24; i++) ok &= fabsf(d[i]) <= 32.f;
    scale(-r0, -r1);
  }
  split_d(12);
  wg_fence();
#pragma unroll
  for (int s = 0; s < 3; s++) {
    if (s == 0) mma64_rs<0, 1>(d, fh, desc_sw128(tX));
    else mma64_rs<1, 1>(d, fh + 4 * s, desc_sw128(tX) + 128 * s);
    mma64_rs<1, 1>(d, fl + 4 * s, desc_sw128(tX) + 128 * s);
  }
  mma64_done(d);
  split_d(16);
#pragma unroll
  for (int g = 0; g < 4; g++) {
    const uint32_t c = (16 * (wr & 3) + (lane & 15)) * 128 + (((2 * g + (lane >> 4)) ^ (lane & 7)) << 4);
    stsm_x4(tH + c, fh[4 * g], fh[4 * g + 1], fh[4 * g + 2], fh[4 * g + 3]);
    stsm_x4(tL + c, fl[4 * g], fl[4 * g + 1], fl[4 * g + 2], fl[4 * g + 3]);
  }
  mbar_wait(kS + kBarOff + 64 + 8, 0);
  mbar_wait(kS + kBarOff + 64 + 16 - 16 * z, 0);
  fence_async();
  bar_sync(1 + z, 128);
  wg_fence();
#pragma unroll
  for (int s = 0; s < 3; s++) {
    if (s == 0) mma64_ss<0, -1, 1>(d, desc_sw128(tX), desc_sw128(tH));
    else mma64_ss<1, -1, 1>(d, desc_sw128(tX) + 128 * s, desc_sw128(tH) + 128 * s);
    mma64_ss<1, -1, 1>(d, desc_sw128(tX) + 128 * s, desc_sw128(tL) + 128 * s);
  }
  mma64_done(d);
  store_big(d);
  float dm[32];
  auto mm = [&](uint32_t x, uint32_t y, bool first) {
    const uint64_t da = desc_sw128(z ? y : x), db = desc_sw128(z ? x : y);
    if (first) mma64_ss<0, 1, 1>(dm, da, db); else mma64_ss<1, 1, 1>(dm, da, db);
  };
  wg_fence();
#pragma unroll
  for (int s = 0; s < 3; s++) { mm(kWq + kWv - tX + 2048 * s, tH + 2048 * s, s == 0); mm(kWq + kWv - tX + 2048 * s, tL + 2048 * s, false); }
  wg_commit();
  bar_sync(1 + z, 128);
  if (warp == z) {
    const uint32_t da = big + lane * 512 + ((8 * lane) ^ ((lane & 3) << 6)), db = (da ^ 32) + 260;
    float dx = ldsf(da) + 1.f, dy = ldsf(db) + 1.f;
    sts(da, __float_as_int(dx));
    sts(db, __float_as_int(dy));
    float hx[16], hy[16];
#pragma unroll
    for (int i = 0; i < 16; i++) hx[i] = hy[i] = 0.f;
#pragma unroll 1
    for (int c = 0; c < 16; c += 4) {
#pragma unroll
      for (int e = 3; e >= 0; e--) {
        __syncwarp();
        const int key = __reduce_max_sync(0xffffffffu, max((__float_as_int(dx) & ~63) | (2 * lane), (__float_as_int(dy) & ~63) | (2 * lane + 1)));
        const int p = key & 63;
        const float2 row = ldsf2(big + p * 256 + ((8 * lane) ^ ((p & 7) << 5)));
        float k[16];
#pragma unroll
        for (int i = e == 3; i < 4; i++) {
          const float4 v = ldsf4(gt + p * 144 + 48 - 4 * c + 16 * i);
          k[4 * i] = v.x; k[4 * i + 1] = v.y; k[4 * i + 2] = v.z; k[4 * i + 3] = v.w;
        }
        const float is = rsq(__int_as_float(key));
        float ux[4] = {row.x, 0.f, 0.f, 0.f}, uy[4] = {row.y, 0.f, 0.f, 0.f};
#pragma unroll
        for (int i = e + 1; i < 16; i++) { ux[i >> 2] = fmaf(-k[i], hx[i], ux[i >> 2]); uy[i >> 2] = fmaf(-k[i], hy[i], uy[i >> 2]); }
        hx[e] = ((ux[0] + ux[1]) + (ux[2] + ux[3])) * is;
        hy[e] = ((uy[0] + uy[1]) + (uy[2] + uy[3])) * is;
        dx = fmaf(-hx[e], hx[e], dx);
        dy = fmaf(-hy[e], hy[e], dy);
        sts(gt + lane * 288 + 48 - 4 * c + 4 * e, __float_as_int(hx[e]));
        sts(gt + lane * 288 + 192 - 4 * c + 4 * e, __float_as_int(hy[e]));
        ok &= key >= 0x3c000000;
      }
#pragma unroll
      for (int i = 15; i >= 4; i--) { hx[i] = hx[i - 4]; hy[i] = hy[i - 4]; }
    }
    ok &= fmaxf(fabsf(dx), fabsf(dy)) <= 0x1p-10f;
  } else if (warp >= 2) {
#pragma unroll 1
    for (int h = 0; h < 2; h++) {
      const int row = (t & 63) + 64 * h;
      float a = 0.f, b = 0.f;
#pragma unroll 2
      for (int c = 0; c < 8; c++) {
        const int4 v = lds4(tX + row * 128 + ((c ^ (t & 7)) << 4));
        const uint32_t w[4] = {(uint32_t)v.x, (uint32_t)v.y, (uint32_t)v.z, (uint32_t)v.w};
#pragma unroll
        for (int k = 0; k < 4; k++) { a = fmaf(bf_lo(w[k]), bf_lo(w[k]), a); b = fmaf(bf_hi(w[k]), bf_hi(w[k]), b); }
      }
      sts(n2 + 4 * row, __float_as_int(a + b));
    }
    bar_sync(8 + z, 64);
    const float s = warp_sum(ldsf(n2 + 4 * lane) + (lane < 16 ? ldsf(n2 + 128 + 4 * lane) : 0.f)) * (1.f / 48);
    if (t == 64) sts(n2 + 1020, __float_as_int(s));
  }
  bar_sync(1 + z, 128);
  const float s2 = ldsf(n2 + 1020);
  ok &= (s2 >= 0x1p-60f) & (s2 <= 0x1p60f);
  {
    const float4 gx = ldsf4(gt + lane * 288 + 16 * warp), gy = ldsf4(gt + lane * 288 + 144 + 16 * warp);
    const float vx[4] = {gx.x, gx.y, gx.z, gx.w}, vy[4] = {gy.x, gy.y, gy.z, gy.w};
    float k = rsq(s2);
#pragma unroll 1
    for (int h = 0; h < 2; h++) {
#pragma unroll
      for (int i = 0; i < 4; i++) {
        uint32_t hi, lo;
        const uint32_t o = 6144 + 2048 * h + (4 * warp + i) * 128 + ((4 * lane) ^ (((4 * warp + i) & 7) << 4));
        split2(vx[i] * k, vy[i] * k, hi, lo);
        sts(tH + o, hi);
        sts(tL + o, lo);
      }
      k *= s2;
    }
  }
  fence_async();
  __syncthreads();
  wg_fence();
  mm(tile_hi(1 - z) + 8192, tH + 6144, false); mm(tile_hi(1 - z) + 8192, tL + 6144, false); mm(tile_lo(1 - z) + 8192, tH + 6144, false);
  wg_commit();
  const float so = ldsf(kS + kTmpOff + (1 - z) * 1024 + 1020);
  ok &= z | (ldsf(kS + kTmpOff + 4 * t) * so <= 6.f * s2 * ldsf(kS + kTmpOff + 1024 + 4 * t));
  wg_wait<0>();
  asm volatile("" : D32_OPS("+f", dm)::"memory");
  float nn = 0.f;
#pragma unroll
  for (int i = 0; i < 32; i++) { nn = fmaf(dm[i], dm[i], nn); d[i] = dm[i] * (z ? kC : 1.f); }
  split_d(16);
  {
    const uint64_t db = desc_sw128(z ? kWk : kWq);
    float d2[32];
    wg_fence();
#pragma unroll
    for (int s = 0; s < 4; s++) {
      if (s == 0) mma64_rs<0, 0>(d2, fh, db + 512); else mma64_rs<1, 0>(d2, fh + 4 * s, db + 512 + 2 * s);
      mma64_rs<1, 0>(d2, fl + 4 * s, db + 512 + 2 * s);
    }
    wg_commit();
#pragma unroll
    for (int s = 0; s < 4; s++) {
      if (s == 0) mma64_rs<0, 0>(d, fh, db); else mma64_rs<1, 0>(d, fh + 4 * s, db + 2 * s);
      mma64_rs<1, 0>(d, fl + 4 * s, db + 2 * s);
    }
    wg_commit();
    ok &= warp_sum(nn) * s2 <= 128.f * so;
    auto out = [&](const float* x, int s) {
      if (s >= 3 || z) dst[s * 128] = make_uint4(pack_bf16(x[0], x[1]), pack_bf16(x[2], x[3]), pack_bf16(x[4], x[5]), pack_bf16(x[6], x[7]));
    };
    wg_wait<1>();
    asm volatile("" : D32_OPS("+f", d2)::"memory");
#pragma unroll
    for (int s = 0; s < 4; s++) out(d2 + 8 * s, 4 + s);
    wg_wait<0>();
    asm volatile("" : D32_OPS("+f", d)::"memory");
#pragma unroll
    for (int s = 0; s < 4; s++) out(d + 8 * s, s);
  }
  const int all = __syncthreads_and(ok);
  if (threadIdx.x == 192) {
    asm volatile("st.release.gpu.global.u32 [%0], %1;\n" ::"l"(g_state + blockIdx.x), "r"(2 * epoch + 2 + (all != 0)) : "memory");
    if (atomicInc(&g_seen, gridDim.x - 1) == gridDim.x - 1) g_epoch = epoch + 1;
  }
}

template <int V> struct IC { __device__ constexpr operator int() const { return V; } };
struct WPtrs { const uint8_t* p[4]; };

__global__ void __launch_bounds__(256, 1)
autoint_kernel(const __grid_constant__ CUtensorMap tm_e, const __grid_constant__ CUtensorMap tm_o,
               const __grid_constant__ CUtensorMap tm_q, const __grid_constant__ CUtensorMap tm_k,
               const __grid_constant__ CUtensorMap tm_v, const __grid_constant__ CUtensorMap tm_r,
               const uint8_t* p_e, const __grid_constant__ WPtrs pw,
               const int grid, const int n_base, const int n_extra, const int n_skip, const int zero, const int n_open) {
  extern __shared__ __align__(1024) uint8_t smem[];
  const int tid = threadIdx.x;
  if ((tid & 31) == 0 && tid >= 64) asm volatile("prefetch.tensormap [%0];\n" ::"l"((const char*)&tm_e + (tid - 64) * 4) : "memory");
  if (tid < 200) asm volatile("prefetch.global.L2 [%0];\n" ::"l"(p_e + max(((int)blockIdx.x & ~1) - 2, 0) * (kF * kD * 2) + tid * 128) : "memory");
  else if (tid < 208) asm volatile("prefetch.global.L2 [%0];\n" ::"l"(pw.p[(blockIdx.x >> 5) & 3] + (blockIdx.x & 31) * 1024 + (tid & 7) * 128) : "memory");
  constexpr uint32_t bar_full = kS + kBarOff;
  constexpr uint32_t bar_w = kS + kBarOff + 64;
  const int cta = blockIdx.x - 2;
  const int n_tiles = n_base + (cta < n_extra) - (cta >= grid - 2 ? n_skip : 0);
  auto row_of = [&](int t) { return (t * grid + cta) * kF; };
  auto load_r = [&](int row, int st, uint32_t bar) {
    mbar_expect_tx(bar, kETx);
    tma_load_2d(kS + st * kEStage, &tm_e, 0, row, bar);
    tma_load_2d(kS + st * kEStage + kEHalf, &tm_e, 64, row, bar);
  };

  auto load_w = [&](int w, int m) {
    const int h = w ^ (cta & 1);
    const uint32_t dst = kS + kWGBase + w * kWGRegion, bar = bar_w + 8 * (4 * w + m);
    mbar_expect_tx(bar, 16384);
    if (m == 0) tma_load_2d(dst, &tm_q, 0, h * 128, bar);
    if (m == 1) tma_load_2d(dst + 16384, &tm_k, 0, h * 128, bar);
    if (m == 2) tma_load_2d(kS + (1 + w) * kEStage, &tm_v, 0, h * 128, bar);
    if (m == 3) tma_load_2d(dst + kWsOff, &tm_r, h * 64, 0, bar);
  };
  if (tid == 0) {
    mbar_init(bar_w + 80, 1);
    mbar_init(bar_w, 1);
    mbar_init(bar_w + 8, 1);
    mbar_init(bar_w + 16, 1);
    asm volatile("fence.mbarrier_init.release.cluster;\n" ::: "memory");
    fence_async();
    load_w(0, 0); load_w(0, 1); load_w(0, 2);
    if (cta >= 0) load_r((cta & ~1) * kF, 3, bar_w + 80);
  } else if (tid == 32) {
    if (smem_u32(smem) != kS) __trap();
    for (int s = 0; s < kStages; s++) mbar_init(bar_full + 8 * s, 1);
    for (int s = 3; s < 10; s++) mbar_init(bar_w + 8 * s, 1);
    for (int s = 0; s < 2; s++) mbar_init(bar_full + 32 + 8 * s, 1);
    asm volatile("fence.mbarrier_init.release.cluster;\n" ::: "memory");
  }
  const int wg_r = __shfl_sync(0xffffffffu, tid >> 7, 0);
  const int warp = __shfl_sync(0xffffffffu, (tid >> 5) & 3, 0);
  const int lane = tid & 31;
  auto st_zero = [&](uint32_t a) { asm volatile("st.shared.v4.u32 [%0], {%1,%1,%1,%1};\n" ::"r"(a), "r"(0) : "memory"); };
  if (tid >= 128) st_zero(kS + (warp + (warp & 2) * 2) * kEHalf + kF * 128 + lane * 16);
  fence_async();
  __syncthreads();
  if (blockIdx.x < 2) {
    transform_weights(wg_r, warp);
    if (zero == 0) return;
  } else {
    if (tid == 128) {
      load_w(1, 0); load_w(1, 1); load_w(1, 2); load_w(0, 3);
      load_r((cta | 1) * kF, 0, bar_full);
      load_w(1, 3);
    }
    if (tid >= 224 && tid < 228) sts4(kS + kBadOff + 16 * (tid - 224), 0, 0, 0, 0);
    if (tid == 160) {
      const int mod = max(n_open, 1), x = (cta >> 1) % mod, y = x - (n_open - 2 * n_skip);
      sts(kS + kOpenOff, 0);
      sts(kS + kOpenOff + 4, (n_open == 0 ? kB : y < 0 ? n_base * grid + x : (n_base - (y >> 1)) * grid - 2 + (y & 1)) * kF);
      const uint64_t ga = (uint64_t)__cvta_generic_to_global(g_claim + 2 * x + (cta & 1));
      sts4(kS + kClaimOff, (int)ga, (int)(ga >> 32), ((grid >> 1) - 1 - x) / mod, n_open ? n_tiles + 1 : 0);
    }
    if (tid == 192) sts(kS + kOpenOff + 8, 2 * *(volatile unsigned*)&g_epoch + 2);

    int it = -1;
    bool fast = false;
    uint32_t ln = lane;
    uint32_t wQ[32], wK[32], wV[32], vf[26];
    float acc1[52], acc2[52];
    uint32_t z0 = 0, z1 = 0;
    uint32_t t_addr = kS + kWGBase + (tid >> 7) * kWGRegion + ((lane >> 4) * 8 + (lane & 7)) * 128 + (((2 * warp + ((lane >> 3) & 1)) ^ (lane & 7)) << 4);
    const uint32_t q12_k = (2 * (lane >> 4) + ((lane >> 2) & 1) + 2 * (lane & 3)) & 7;
    uint32_t q12_addr = kS + kWGBase + (tid >> 7) * kWGRegion + kQOff + (9 + 2 * (lane & 3)) * 1024 + q12_k * 128 + (((2 * warp + ((lane >> 3) & 1)) ^ q12_k) << 4);
    asm volatile("xor.b32 %0, %0, %2;\nxor.b32 %1, %1, %2;\n" : "+r"(t_addr), "+r"(q12_addr) : "r"(zero));
    auto tail_inv = [&]() { return (ln & 2) != 0; };
    auto publish = [&](int wg) {
      bar_sync(1 + wg, 128);
      fence_async();
    };
    auto tma_out = [&](int wg, int row) {
      tma_store_2d(&tm_o, kS + kWGBase + wg * kWGRegion + kOOff, (wg ^ (cta & 1)) * 64, row);
      asm volatile("cp.async.bulk.commit_group;\n" ::: "memory");
    };

    auto iter = [&](auto wgc, auto fastc) __attribute__((always_inline)) {
      constexpr bool FAST = fastc;
      constexpr int wg = wgc;
      constexpr int kLag = 3, kRJ = FAST ? 9 : 11;
      constexpr uint32_t wgb = kS + kWGBase + wg * kWGRegion, bar_peek = bar_full + 32 + 8 * wg;
      const uint64_t dQ = desc_sw128(wgb + kQOff), dK = desc_sw128(wgb + kKOff), dP = desc_p(wgb + kPOff), dW = desc_sw128(wgb + kWsOff);
      auto p8_addr = [&]() { return wgb + kPOff + 3 * warp * kPGrp + ln * 16 + (kPL - 128) / 8 * (ln & 24); };
      auto cvt_v = [&]() {
#pragma unroll
        for (int i = 0; i < 26; i++) vf[i] = pack_bf16(acc2[2 * i], acc2[2 * i + 1]);
        asm volatile("and.b32 %0, %2, %3;\nand.b32 %1, %4, %3;\n" : "=r"(z0), "=r"(z1) : "r"(vf[0]), "r"(zero), "r"(vf[1]));
      };
      it++;
      const bool change = !FAST && it == (cta >= grid - 2 ? 1 : kSwitch);
      const bool own = !FAST && wg == 0 && it == 0;
      const int stage = own ? 3 : it & 3;
      const uint64_t dE = desc_sw128(kS) + (uint64_t)((stage * kEStage) >> 4);
      if (FAST || it > 0) {
        wg_fence();
        issue_pv(acc1, vf, dP, z0, z1);
        wg_commit();
      }
      mbar_wait(own ? bar_w + 80 : bar_full + 8 * stage, (it >> 2) & 1);
      wg_fence();
      proj(acc2, wQ, dE);
      wg_commit();
      if (wg == 1 && warp == kRefill && ln == 0 && (FAST || it >= 1) && it + kStages - 2 < n_tiles) {
        const int ps = (it - 1) & (kStages - 1);
        if (!FAST && it == 1) load_r(row_of(3), 3, bar_full + 24);
        load_r(it + kStages - 1 < n_tiles ? row_of(it + kStages - 1) : lds(kS + kOpenOff + 4), ps, bar_full + 8 * ps);
      }
      if (wg == 0 && it + 1 == n_tiles && ln == 0) {
        if (warp == kRefill) {
          const int4 c = lds4(kS + kClaimOff);
          uint32_t k;
          asm volatile("atom.global.inc.u32 %0, [%1], %2;\n" : "=r"(k) : "l"((uint64_t)(uint32_t)c.x | ((uint64_t)(uint32_t)c.y << 32)), "r"(c.z) : "memory");
          if (k == 0) sts(kS + kOpenOff, c.w);
        }
        if (warp == 1 && atomicInc(&g_seen, grid + 1) == grid + 1) g_epoch = (unsigned)lds(kS + kOpenOff + 8) / 2;
      }
      wg_wait<1>();
      fence_acc(acc1);
      store_t<true>(acc1, t_addr + kOOff);
      wg_fence();
      proj(acc1, wK, dE);
      wg_commit();
      if (!FAST && it == 0 && warp == kElect && ln == 0) load_r(row_of(1 + wg), 1 + wg, bar_full + 8 * (1 + wg));
      wg_wait<1>();
      fence_acc(acc2);
      store_q_t(acc2, t_addr, t_addr + (ln & 16) * 64, q12_addr, ln & 29);
      wg_fence();
      if (FAST) proj_v(acc2, wV, dE); else proj<true>(acc2, wV, dE);
      wg_commit();
      bar_arrive(4 - wg, 256);
      if (change && warp == kElect && ln == 0) {
        mbar_expect_tx(bar_peek, 16);
        asm volatile("cp.async.bulk.shared::cluster.global.mbarrier::complete_tx::bytes [%0], [%1], 16, [%2];\n" ::"r"(kS + kPeekOff + 16 * wg), "l"(g_state), "r"(bar_peek) : "memory");
      }
      wg_wait<1>();
      fence_acc(acc1);
      store_t<false>(acc1, t_addr + kKOff);
      if (FAST) {
        wg_wait<0>();
        fence_acc(acc2);
        cvt_v();
#pragma unroll
        for (int i = 0; i < 26; i++) asm volatile("" : "+r"(vf[i]));
        sched_barrier();
      }
      publish(wg);
      wg_fence();
      issue_s(acc1, dQ + 512, dK);
      wg_commit();
      if (!FAST) {
        wg_wait<1>();
        fence_acc(acc2);
        cvt_v();
        wg_fence();
      }
      issue_s(acc2, dQ, dK);
      wg_commit();
      if (warp == kElect && ln == 0 && (FAST || it > 0)) tma_out(wg, !FAST && it == 1 ? ((cta & ~1) | wg) * kF : row_of(it - 1));
      wg_wait<1>();
      fence_acc(acc1);
      const float zf = __int_as_float(zero);
      auto q3_dep = [&](const Q3& q, float later) { return ((fmaf(later, zf, q.t) + q.s1) + q.s2) + q.s3; };
      float x[4];
      {
        const bool b0 = ln & 4, b1 = ln & 8, b2 = ln & 16;
#pragma unroll
        for (int h = 0; h < 2; h++) {
          const float* v = acc1 + 2 + h;
          const float x01 = b0 ? v[4] : v[0], x23 = b0 ? v[12] : v[8], x45 = b0 ? v[20] : v[16], x67 = b0 ? v[28] : v[24];
          const float x03 = b1 ? x23 : x01, x47 = b1 ? x67 : x45;
          x[h] = b2 ? x47 : x03;
          const float y01 = b0 ? v[36] : v[32], y23 = b0 ? v[44] : v[40];
          const float y03 = b1 ? y23 : y01;
          x[2 + h] = b2 ? v[48] : y03;
        }
#pragma unroll
        for (int h = 0; h < 4; h++) x[h] = ex2(x[h]);
      }
      float sd = x[0] + x[1];
      if (ln < 18) sd += x[2] + x[3];
      Q3 qd = q3_start(sd, 1);
      float sc;
#pragma unroll
      for (int j = 0; j < 7; j++) set_exp<0>(acc1, j, sc, tail_inv());
      qd = q3_start(q3_dep(qd, sc), 4);
#pragma unroll
      for (int j = 7; j < 12; j++) set_exp<0>(acc1, j, sc, tail_inv());
      sd = q3_dep(qd, sc);
      set_exp<0>(acc1, 12, sc, tail_inv());
      const Q3 qc = q3_start(sc, 1);
      const float sd2 = __shfl_xor_sync(0xffffffffu, sd, 16);
      sched_barrier();
      wg_wait<0>();
      fence_acc(acc2);
      if (change) {
        const int head = wg ^ (cta & 1);
        const unsigned tag = lds(kS + kOpenOff + 8);
        mbar_wait(bar_peek, 0);
        unsigned s0 = lds(kS + kPeekOff + 16 * wg) - tag, s1 = lds(kS + kPeekOff + 16 * wg + 4) - tag;
        if ((s0 | s1) > 1) {
          for (int n = 0; (s0 | s1) > 1 && n < 4096; n++) {
            asm volatile("ld.relaxed.gpu.global.v2.u32 {%0,%1}, [%2];\n" : "=r"(s0), "=r"(s1) : "l"(g_state) : "memory");
            s0 -= tag; s1 -= tag;
          }
          asm volatile("{.reg .pred p, q;\nsetp.le.u32 q, %1, 1;\nbar.red.and.pred p, %2, 128, q;\nselp.b32 %0, %0, 0, p;}\n" : "+r"(s0) : "r"(s0 | s1), "n"(1 + wg) : "memory");
        }
        fast = __any_sync(0xffffffffu, s0 & s1);
        if (fast) {
          const uint4* src = &g_w[head][0][warp * 32 + ln];
#pragma unroll
          for (int i = 0; i < 13; i++) {
            uint32_t* w = i < 5 ? wQ + 12 + 4 * i : wK + 4 * (i - 5);
            asm volatile("ld.relaxed.gpu.global.v4.u32 {%0,%1,%2,%3}, [%4];\n" : "=r"(w[0]), "=r"(w[1]), "=r"(w[2]), "=r"(w[3]) : "l"(src + i * 128) : "memory");
          }
        }
      }
      float sa, sb;
#pragma unroll
      for (int j = 0; j < kLag; j++) set_exp<0>(acc2, j, sa, tail_inv());
      sc = q3_dep(qc, sa);
      bool bad = out_of_range<FAST>(sc);
      const float ic = rcp(sc);
      {
        sd = fmaf(sa, zf, sd) + sd2;
        bad |= out_of_range<FAST>(sd);
        const float id = rcp(sd);
        stsm_x2(wgb + kPOff + 12 * kPGrp + warp * 16 + ln * kPL, pack_bf16(x[0] * id, x[1] * id), pack_bf16(x[2] * id, x[3] * id));
      }
#pragma unroll
      for (int c = 0; c < 4; c++) norm_set<0>(acc1, c, ic, p8_addr() + 2 * kPGrp);
#pragma unroll
      for (int j = kLag; j < 13; j++) set_exp<0>(acc2, j, sa, tail_inv());
      const Q3 qa = q3_start(sa, 1);
      sched_barrier();
#pragma unroll
      for (int j = 0; j < kLag; j++) set_exp<2>(acc2, j, sb, tail_inv());
      sa = q3_dep(qa, sb);
      bad |= out_of_range<FAST>(sa);
      const float ia = rcp(sa);
#pragma unroll
      for (int c = 0; c < 4; c++) norm_set<0>(acc2, c, ia, p8_addr());
#pragma unroll
      for (int j = kLag; j < kRJ; j++) set_exp<2>(acc2, j, sb, tail_inv());
      PIN(sb);
      sched_barrier();
      if (!FAST && it == 0) mbar_wait(bar_w + 8 * (4 * wg + 3), 0);
      asm volatile("cp.async.bulk.wait_group.read 0;\n" ::: "memory");
      if (wg == 1 || it < n_tiles) bar_sync(3 + wg, 256);
      wg_fence();
      proj_r<FAST, true>(acc1, wV, dE, dW);
      wg_commit();
      sched_barrier();
#pragma unroll
      for (int j = kRJ; j < 13; j++) set_exp<2>(acc2, j, sb, tail_inv());
      sb = q3_end(q3_start(sb, 1));
      bad |= out_of_range<FAST>(sb);
      const float ib = rcp(sb);
#pragma unroll
      for (int c = 0; c < 4; c++) norm_set<2>(acc2, c, ib, p8_addr() + kPGrp);
      asm volatile("{.reg .pred p;\nsetp.ne.u32 p, %1, 0;\n@p st.shared.u8 [%0], %1;}\n" ::"r"(kS + kBadOff + 32 * wg + min(it, 31)), "r"((uint32_t)bad) : "memory");
      wg_wait<0>();
      fence_acc(acc1);
      publish(wg);
      asm volatile("xor.b32 %0, %0, %1;\n" : "+r"(ln) : "r"(zero));
    };
    auto loops = [&](auto wgc) __attribute__((always_inline)) {
      auto won = [&]() { return it + 1 < lds(kS + kOpenOff); };
      do iter(wgc, IC<0>()); while (!fast && (it + 1 < n_tiles || (wgc == 0 && won())));
      if (fast) {
#pragma unroll
        for (int i = 0; i < 12; i++) wQ[i] = wV[i];
#pragma unroll
        for (int i = 12; i < 32; i++) asm("sub.rn.bf16x2 %0, %0, %1;\n" : "+r"(wV[i]) : "r"(wQ[i]));
#pragma unroll
        for (int s = 0; s < 3; s++) ldsm_x4_t(t_addr + kWsOff + s * 2048, wV[4 * s], wV[4 * s + 1], wV[4 * s + 2], wV[4 * s + 3]);
        do iter(wgc, IC<1>()); while (it + 1 < n_tiles || (wgc == 0 && won()));
      }
    };

    auto load_frags = [&](uint32_t (&w)[32], int m) {
      mbar_wait(bar_w + 8 * (4 * wg_r + m), 0);
      const uint32_t a = m < 2 ? t_addr + m * 16384 : t_addr - (kWGBase - kEStage) - (tid >> 7) * (kWGRegion - kEStage);
#pragma unroll
      for (int s = 0; s < 8; s++) ldsm_x4_t(a + s * 2048, w[4 * s], w[4 * s + 1], w[4 * s + 2], w[4 * s + 3]);
    };
    load_frags(wQ, 0);
    scale_wq(wQ);
    load_frags(wK, 1);
    load_frags(wV, 2);
    bar_sync(1 + wg_r, 128);
    if (warp < 2) st_zero(kS + (2 + 2 * wg_r + warp) * kEHalf + kF * 128 + lane * 16);
    if (tid >= 156) {
      const uint8_t* p = p_e + (size_t)(3 * grid + cta) * (kF * kD * 2) + (tid - 156) * 256;
      asm volatile("prefetch.global.L2 [%0];\nprefetch.global.L2 [%0 + 128];\n" ::"l"(p));
    }
    if (wg_r == 1) bar_sync(4, 256);
#pragma unroll
    for (int i = 0; i < 52; i++) asm volatile("" : "=f"(acc1[i]));
#pragma unroll
    for (int i = 0; i < 26; i++) asm volatile("" : "=r"(vf[i]));
    if (wg_r == 1) loops(IC<1>()); else loops(IC<0>());

    int tid2;
    asm volatile("mov.u32 %0, %tid.x;\n" : "=r"(tid2));
    const int wg = __shfl_sync(0xffffffffu, tid2 >> 7, 0);
    wg_fence();
    issue_pv(acc1, vf, desc_p(kS + kWGBase + wg * kWGRegion + kPOff), z0, z1);
    wg_commit();
    if (wg == 0 && it < n_tiles) bar_arrive(4, 256);
    wg_wait<0>();
    fence_acc(acc1);
    store_t<true>(acc1, t_addr + kOOff);
    publish(wg);
    if (warp == kElect && ln == 0) tma_out(wg, it == n_tiles ? lds(kS + kOpenOff + 4) : row_of(it));
    if (tid2 == 64) mbar_wait(bar_full + 8 * (n_tiles & 3), (n_tiles >> 2) & 1);
    __syncthreads();
    if (!__any_sync(0xffffffffu, lds16(kS + kBadOff + 2 * ln))) {
      asm volatile("cp.async.bulk.wait_group.read 0;\n" ::: "memory");
      return;
    }
  }
  exact_redo(&tm_e, &tm_o, &tm_q, &tm_k, &tm_v, n_tiles);
}

typedef CUresult (*EncodeFn)(CUtensorMap*, CUtensorMapDataType, cuuint32_t, void*, const cuuint64_t*, const cuuint64_t*,
                             const cuuint32_t*, const cuuint32_t*, CUtensorMapInterleave, CUtensorMapSwizzle,
                             CUtensorMapL2promotion, CUtensorMapFloatOOBfill);

}

extern "C" void kernel_launch(void* const* d_in, const int* in_sizes, int n_in, void* d_out, int out_size) {
  static EncodeFn encode = nullptr;
  static int num_sms = 0;
  if (!encode) {
    void* fn = nullptr;
    cudaDriverEntryPointQueryResult qres;
    cudaGetDriverEntryPoint("cuTensorMapEncodeTiled", &fn, cudaEnableDefault, &qres);
    encode = (EncodeFn)fn;
    int dev = 0;
    cudaGetDevice(&dev);
    cudaDeviceGetAttribute(&num_sms, cudaDevAttrMultiProcessorCount, dev);
    cudaFuncSetAttribute(autoint_kernel, cudaFuncAttributeMaxDynamicSharedMemorySize, kSmemBytes);
  }
  auto make = [&](void* p, uint64_t cols, uint64_t rows, uint32_t box_rows, CUtensorMapL2promotion promo) {
    CUtensorMap tm;
    cuuint64_t dims[2] = {cols, rows};
    cuuint64_t strides[1] = {cols * 2};
    cuuint32_t box[2] = {64, box_rows};
    cuuint32_t estr[2] = {1, 1};
    encode(&tm, CU_TENSOR_MAP_DATA_TYPE_BFLOAT16, 2, p, dims, strides, box, estr, CU_TENSOR_MAP_INTERLEAVE_NONE,
           CU_TENSOR_MAP_SWIZZLE_128B, promo, CU_TENSOR_MAP_FLOAT_OOB_FILL_NONE);
    return tm;
  };
  const CUtensorMap tm_e = make(d_in[0], kD, (uint64_t)kB * kF, kF, CU_TENSOR_MAP_L2_PROMOTION_L2_256B);
  const CUtensorMap tm_o = make(d_out, kD, (uint64_t)kB * kF, kF, CU_TENSOR_MAP_L2_PROMOTION_NONE);
  const CUtensorMap tm_q = make(d_in[1], 64, 256, 128, CU_TENSOR_MAP_L2_PROMOTION_L2_256B);
  const CUtensorMap tm_k = make(d_in[2], 64, 256, 128, CU_TENSOR_MAP_L2_PROMOTION_L2_256B);
  const CUtensorMap tm_v = make(d_in[3], 64, 256, 128, CU_TENSOR_MAP_L2_PROMOTION_L2_256B);
  const CUtensorMap tm_r = make(d_in[4], 128, 128, 128, CU_TENSOR_MAP_L2_PROMOTION_L2_256B);
  const int grid = (num_sms < 2 ? 2 : num_sms < kB / 8 ? num_sms : kB / 8) & ~1;
  const int n_base = kB / grid, rem = kB - n_base * grid, split = 2 * (rem + 2 * kSkip) <= grid;
  autoint_kernel<<<grid + 2, 256, kSmemBytes>>>(tm_e, tm_o, tm_q, tm_k, tm_v, tm_r, (const uint8_t*)d_in[0],
                                             WPtrs{{(const uint8_t*)d_in[1], (const uint8_t*)d_in[2], (const uint8_t*)d_in[3], (const uint8_t*)d_in[4]}},
                                             grid, n_base, split ? 0 : rem, split ? kSkip : 0, 0, split ? rem + 2 * kSkip : 0);
}
```

```cpp
#include <cuda_runtime.h>
#include <cuda_bf16.h>
#include <cuda.h>
#include <stdint.h>

namespace {

constexpr int kB = 4096, kF = 100, kD = 128;
constexpr int kStages = 4;
constexpr int kElect = 3, kRefill = 2;
constexpr int kSwitch = 3;
constexpr int kSkip = 4;
constexpr uint32_t kS = 1024;
constexpr int kEHalf = 104 * 128;
constexpr int kEStage = 2 * kEHalf;
constexpr int kETx = 2 * kF * 128;
constexpr int kOOff = 0;
constexpr int kQOff = 13312;
constexpr int kKOff = kQOff + 16384;
constexpr int kPOff = kQOff;
constexpr int kPL = 144;
constexpr int kPGrp = 13 * kPL;
constexpr int kWsOff = kKOff + 13312;
constexpr int kWGRegion = kWsOff + 16384;
constexpr int kWGBase = kStages * kEStage;
constexpr int kBarOff = kWGBase + 2 * kWGRegion;
constexpr int kOpenOff = kBarOff + 256;
constexpr int kClaimOff = kBarOff + 272;
constexpr int kBadOff = kBarOff + 320;
constexpr int kPeekOff = kBarOff + 384;
constexpr int kTmpOff = kBarOff + 512;
constexpr int kSmemBytes = kTmpOff + 2 * 1024;
static_assert(kWGRegion % 1024 == 0 && kQOff % 1024 == 0 && kKOff % 1024 == 0 && kWsOff % 1024 == 0 && kWGBase % 1024 == 0 &&
              kPOff + 12 * kPGrp + 16 * kPL <= kWsOff && kSmemBytes <= 232448, "smem layout");

__device__ unsigned g_claim[512];
__device__ uint4 g_w[2][13][128];
__device__ __align__(16) unsigned g_state[4];
__device__ unsigned g_seen, g_epoch;

__device__ __forceinline__ uint32_t smem_u32(const void* p) { return (uint32_t)__cvta_generic_to_shared(p); }

__device__ __forceinline__ void wg_fence() { asm volatile("wgmma.fence.sync.aligned;\n" ::: "memory"); }
__device__ __forceinline__ void wg_commit() { asm volatile("wgmma.commit_group.sync.aligned;\n" ::: "memory"); }
template <int N> __device__ __forceinline__ void wg_wait() { asm volatile("wgmma.wait_group.sync.aligned %0;\n" ::"n"(N) : "memory"); }
__device__ __forceinline__ void fence_async() { asm volatile("fence.proxy.async.shared::cta;\n" ::: "memory"); }
__device__ __forceinline__ void bar_sync(int id, int n) { asm volatile("bar.sync %0, %1;\n" ::"r"(id), "r"(n) : "memory"); }
__device__ __forceinline__ void bar_arrive(int id, int n) { asm volatile("bar.arrive %0, %1;\n" ::"r"(id), "r"(n) : "memory"); }

#define ACC_REGS "{%0,%1,%2,%3,%4,%5,%6,%7,%8,%9,%10,%11,%12,%13,%14,%15,%16,%17,%18,%19,%20,%21,%22,%23,%24,%25," \
                 "%26,%27,%28,%29,%30,%31,%32,%33,%34,%35,%36,%37,%38,%39,%40,%41,%42,%43,%44,%45,%46,%47,%48,%49,%50,%51}"
#define ACC_OPS(c, d)                                                                                        \
  c(d[0]), c(d[1]), c(d[2]), c(d[3]), c(d[4]), c(d[5]), c(d[6]), c(d[7]), c(d[8]), c(d[9]), c(d[10]),        \
  c(d[11]), c(d[12]), c(d[13]), c(d[14]), c(d[15]), c(d[16]), c(d[17]), c(d[18]), c(d[19]), c(d[20]),        \
  c(d[21]), c(d[22]), c(d[23]), c(d[24]), c(d[25]), c(d[26]), c(d[27]), c(d[28]), c(d[29]), c(d[30]),        \
  c(d[31]), c(d[32]), c(d[33]), c(d[34]), c(d[35]), c(d[36]), c(d[37]), c(d[38]), c(d[39]), c(d[40]),        \
  c(d[41]), c(d[42]), c(d[43]), c(d[44]), c(d[45]), c(d[46]), c(d[47]), c(d[48]), c(d[49]), c(d[50]), c(d[51])

#define H4(d, i) "+f"(d[i]), "+f"(d[i + 1]), "=f"(d[i + 2]), "=f"(d[i + 3])
#define ACC_HALF(d) H4(d, 0), H4(d, 4), H4(d, 8), H4(d, 12), H4(d, 16), H4(d, 20), H4(d, 24), H4(d, 28), H4(d, 32), H4(d, 36), H4(d, 40), H4(d, 44), H4(d, 48)

__device__ __forceinline__ void fence_acc(float (&d)[52]) {
  asm volatile("" : ACC_OPS("+f", d)::"memory");
}

template <bool ACC>
__device__ __forceinline__ void mma_rs(float (&d)[52], uint32_t a0, uint32_t a1, uint32_t a2, uint32_t a3, uint64_t db) {
  if constexpr (ACC) {
    asm volatile("wgmma.mma_async.sync.aligned.m64n104k16.f32.bf16.bf16 " ACC_REGS
                 ", {%52,%53,%54,%55}, %56, 1, 1, 1, 0;\n"
                 : ACC_OPS("+f", d)
                 : "r"(a0), "r"(a1), "r"(a2), "r"(a3), "l"(db));
  } else {
    asm volatile("wgmma.mma_async.sync.aligned.m64n104k16.f32.bf16.bf16 " ACC_REGS
                 ", {%52,%53,%54,%55}, %56, 0, 1, 1, 0;\n"
                 : ACC_OPS("=f", d)
                 : "r"(a0), "r"(a1), "r"(a2), "r"(a3), "l"(db));
  }
}
__device__ __forceinline__ void mma_ss(float (&d)[52], uint64_t da, uint64_t db) {
  asm volatile("wgmma.mma_async.sync.aligned.m64n104k16.f32.bf16.bf16 " ACC_REGS ", %52, %53, 1, 1, 1, 0, 0;\n"
               : ACC_OPS("+f", d)
               : "l"(da), "l"(db));
}
__device__ __forceinline__ void mma_ss_tied(float (&d)[52], uint64_t da, uint64_t db) {
  asm volatile("wgmma.mma_async.sync.aligned.m64n104k16.f32.bf16.bf16 " ACC_REGS ", %52, %53, 0, 1, 1, 0, 0;\n"
               : ACC_OPS("+f", d)
               : "l"(da), "l"(db));
}
template <bool ACC>
__device__ __forceinline__ void mma_ss_ta(float (&d)[52], uint64_t da, uint64_t db) {
  if constexpr (ACC) {
    asm volatile("wgmma.mma_async.sync.aligned.m64n104k16.f32.bf16.bf16 " ACC_REGS ", %52, %53, 1, 1, 1, 1, 0;\n"
                 : ACC_OPS("+f", d)
                 : "l"(da), "l"(db));
  } else {
    asm volatile("wgmma.mma_async.sync.aligned.m64n104k16.f32.bf16.bf16 " ACC_REGS ", %52, %53, 0, 1, 1, 1, 0;\n"
                 : ACC_OPS("=f", d)
                 : "l"(da), "l"(db));
  }
}

__device__ __forceinline__ void mma_ss_ta_half(float (&d)[52], uint64_t da, uint64_t db) {
  asm volatile("wgmma.mma_async.sync.aligned.m64n104k16.f32.bf16.bf16 " ACC_REGS ", %52, %53, 0, 1, 1, 1, 0;\n"
               : ACC_HALF(d)
               : "l"(da), "l"(db));
}
__device__ __forceinline__ uint64_t desc_sw128(uint32_t saddr) {
  return (uint64_t)((saddr & 0x3FFFF) >> 4) | ((uint64_t)1 << 16) | ((uint64_t)(1024 >> 4) << 32) | ((uint64_t)1 << 62);
}
__device__ __forceinline__ uint64_t desc_p(uint32_t saddr) {
  return (uint64_t)((saddr & 0x3FFFF) >> 4) | ((uint64_t)(kPL >> 4) << 16) | ((uint64_t)(kPGrp >> 4) << 32);
}

__device__ __forceinline__ uint32_t pack_bf16(float lo, float hi) {
  uint32_t r;
  asm("cvt.rn.bf16x2.f32 %0, %1, %2;\n" : "=r"(r) : "f"(hi), "f"(lo));
  return r;
}
__device__ __forceinline__ uint32_t pack_bf16_relu(float lo, float hi) {
  uint32_t r;
  asm("cvt.rn.relu.bf16x2.f32 %0, %1, %2;\n" : "=r"(r) : "f"(hi), "f"(lo));
  return r;
}
__device__ __forceinline__ float ex2(float x) {
  float y;
  asm("ex2.approx.ftz.f32 %0, %1;\n" : "=f"(y) : "f"(x));
  return y;
}
__device__ __forceinline__ float rcp(float x) {
  float y;
  asm("rcp.approx.ftz.f32 %0, %1;\n" : "=f"(y) : "f"(x));
  return y;
}
__device__ __forceinline__ float rsq(float x) {
  float y;
  asm("rsqrt.approx.ftz.f32 %0, %1;\n" : "=f"(y) : "f"(x));
  return y;
}
__device__ __forceinline__ void stsm_x4(uint32_t addr, uint32_t r0, uint32_t r1, uint32_t r2, uint32_t r3) {
  asm volatile("stmatrix.sync.aligned.m8n8.x4.shared.b16 [%0], {%1,%2,%3,%4};\n" ::"r"(addr), "r"(r0), "r"(r1), "r"(r2), "r"(r3) : "memory");
}
__device__ __forceinline__ void stsm_x2(uint32_t addr, uint32_t r0, uint32_t r1) {
  asm volatile("stmatrix.sync.aligned.m8n8.x2.shared.b16 [%0], {%1,%2};\n" ::"r"(addr), "r"(r0), "r"(r1) : "memory");
}
__device__ __forceinline__ void stsm_x1(uint32_t addr, uint32_t r0) {
  asm volatile("stmatrix.sync.aligned.m8n8.x1.shared.b16 [%0], {%1};\n" ::"r"(addr), "r"(r0) : "memory");
}
__device__ __forceinline__ void stsm_x4_t(uint32_t addr, uint32_t r0, uint32_t r1, uint32_t r2, uint32_t r3) {
  asm volatile("stmatrix.sync.aligned.m8n8.x4.trans.shared.b16 [%0], {%1,%2,%3,%4};\n" ::"r"(addr), "r"(r0), "r"(r1), "r"(r2), "r"(r3) : "memory");
}
__device__ __forceinline__ void stsm_x2_t(uint32_t addr, uint32_t r0, uint32_t r1) {
  asm volatile("stmatrix.sync.aligned.m8n8.x2.trans.shared.b16 [%0], {%1,%2};\n" ::"r"(addr), "r"(r0), "r"(r1) : "memory");
}
__device__ __forceinline__ void ldsm_x4_t(uint32_t addr, uint32_t& r0, uint32_t& r1, uint32_t& r2, uint32_t& r3) {
  asm volatile("ldmatrix.sync.aligned.m8n8.x4.trans.shared.b16 {%0,%1,%2,%3}, [%4];\n" : "=r"(r0), "=r"(r1), "=r"(r2), "=r"(r3) : "r"(addr) : "memory");
}
__device__ __forceinline__ int lds16(uint32_t addr) {
  uint16_t v;
  asm volatile("ld.shared.u16 %0, [%1];\n" : "=h"(v) : "r"(addr) : "memory");
  return v;
}
__device__ __forceinline__ int lds(uint32_t addr) {
  int v;
  asm volatile("ld.shared.u32 %0, [%1];\n" : "=r"(v) : "r"(addr) : "memory");
  return v;
}
__device__ __forceinline__ int4 lds4(uint32_t addr) {
  int4 v;
  asm volatile("ld.shared.v4.u32 {%0,%1,%2,%3}, [%4];\n" : "=r"(v.x), "=r"(v.y), "=r"(v.z), "=r"(v.w) : "r"(addr) : "memory");
  return v;
}
__device__ __forceinline__ void sts(uint32_t addr, int v) { asm volatile("st.shared.u32 [%0], %1;\n" ::"r"(addr), "r"(v) : "memory"); }
__device__ __forceinline__ void sts4(uint32_t addr, int x, int y, int z, int w) {
  asm volatile("st.shared.v4.u32 [%0], {%1,%2,%3,%4};\n" ::"r"(addr), "r"(x), "r"(y), "r"(z), "r"(w) : "memory");
}
__device__ __forceinline__ void mbar_init(uint32_t bar, int count) {
  asm volatile("mbarrier.init.shared::cta.b64 [%0], %1;\n" ::"r"(bar), "r"(count) : "memory");
}
__device__ __forceinline__ void mbar_expect_tx(uint32_t bar, int bytes) {
  asm volatile("mbarrier.arrive.expect_tx.shared::cta.b64 _, [%0], %1;\n" ::"r"(bar), "r"(bytes) : "memory");
}
__device__ __forceinline__ void mbar_wait(uint32_t bar, uint32_t parity) {
  asm volatile(
      "{\n.reg .pred p;\n"
      "WAIT_%=:\n"
      "mbarrier.try_wait.parity.shared::cta.b64 p, [%0], %1;\n"
      "@p bra DONE_%=;\n"
      "bra WAIT_%=;\n"
      "DONE_%=:\n}\n" ::"r"(bar), "r"(parity) : "memory");
}
__device__ __forceinline__ void tma_load_2d(uint32_t dst, const CUtensorMap* tm, int c0, int c1, uint32_t bar) {
  asm volatile("cp.async.bulk.tensor.2d.shared::cluster.global.mbarrier::complete_tx::bytes [%0], [%1, {%3, %4}], [%2];\n" ::"r"(dst),
               "l"(tm), "r"(bar), "r"(c0), "r"(c1) : "memory");
}
__device__ __forceinline__ void tma_load_2d_stream(uint32_t dst, const CUtensorMap* tm, int c0, int c1, uint32_t bar) {
  asm volatile("cp.async.bulk.tensor.2d.shared::cluster.global.mbarrier::complete_tx::bytes.L2::cache_hint [%0], [%1, {%3, %4}], [%2], %5;\n" ::"r"(dst),
               "l"(tm), "r"(bar), "r"(c0), "r"(c1), "l"(0x12F0000000000000ull) : "memory");
}
__device__ __forceinline__ void tma_store_2d(const CUtensorMap* tm, uint32_t src, int c0, int c1) {
  asm volatile("cp.async.bulk.tensor.2d.global.shared::cta.bulk_group [%0, {%2, %3}], [%1];\n" ::"l"(tm), "r"(src), "r"(c0), "r"(c1) : "memory");
}

__device__ __forceinline__ void mma_rs_tied(float (&d)[52], uint32_t a0, uint32_t a1, uint32_t a2, uint32_t a3, uint64_t db) {
  asm volatile("wgmma.mma_async.sync.aligned.m64n104k16.f32.bf16.bf16 " ACC_REGS ", {%52,%53,%54,%55}, %56, 0, 1, 1, 0;\n"
               : ACC_OPS("+f", d)
               : "r"(a0), "r"(a1), "r"(a2), "r"(a3), "l"(db));
}
template <bool TIED = false>
__device__ __forceinline__ void proj(float (&acc)[52], const uint32_t (&w)[32], uint64_t de) {
#pragma unroll
  for (int s = 0; s < 8; s++) {
    uint64_t db = de + (uint64_t)(((s >> 2) * kEHalf + (s & 3) * 32) >> 4);
    if (s == 0) { if (TIED) mma_rs_tied(acc, w[0], w[1], w[2], w[3], db); else mma_rs<false>(acc, w[0], w[1], w[2], w[3], db); }
    else mma_rs<true>(acc, w[4 * s], w[4 * s + 1], w[4 * s + 2], w[4 * s + 3], db);
  }
}
__device__ __forceinline__ void proj_v(float (&acc)[52], const uint32_t (&w)[32], uint64_t de) {
#pragma unroll
  for (int s = 3; s < 8; s++) {
    uint64_t db = de + (uint64_t)(((s >> 2) * kEHalf + (s & 3) * 32) >> 4);
    mma_rs<true>(acc, w[4 * s], w[4 * s + 1], w[4 * s + 2], w[4 * s + 3], db);
  }
}
__device__ __forceinline__ void mma_rs_half(float (&d)[52], uint32_t a0, uint32_t a1, uint32_t a2, uint32_t a3, uint64_t db) {
  asm volatile("wgmma.mma_async.sync.aligned.m64n104k16.f32.bf16.bf16 " ACC_REGS ", {%52,%53,%54,%55}, %56, 0, 1, 1, 0;\n"
               : ACC_HALF(d)
               : "r"(a0), "r"(a1), "r"(a2), "r"(a3), "l"(db));
}
template <bool REGS, bool HALF>
__device__ __forceinline__ void proj_r(float (&acc)[52], const uint32_t* w, uint64_t de, uint64_t dw) {
#pragma unroll
  for (int s = 0; s < 8; s++) {
    uint64_t db = de + (uint64_t)(((s >> 2) * kEHalf + (s & 3) * 32) >> 4);
    if (REGS && s == 0) mma_rs_half(acc, w[0], w[1], w[2], w[3], db);
    else if (REGS && s < 3) mma_rs<true>(acc, w[4 * s], w[4 * s + 1], w[4 * s + 2], w[4 * s + 3], db);
    else if (s == 0) { if (HALF) mma_ss_ta_half(acc, dw, db); else mma_ss_ta<false>(acc, dw, db); }
    else mma_ss_ta<true>(acc, dw + (uint64_t)(s * 128), db);
  }
}

template <bool RELU>
__device__ __forceinline__ void store_t(const float (&a)[52], uint32_t addr) {
  auto pk = [&](int i) { return RELU ? pack_bf16_relu(a[i], a[i + 1]) : pack_bf16(a[i], a[i + 1]); };
#pragma unroll
  for (int j = 0; j < 12; j += 2) stsm_x4_t(addr + j * 1024, pk(4 * j), pk(4 * j + 2), pk(4 * j + 4), pk(4 * j + 6));
  stsm_x2_t(addr + 12 * 1024, pk(48), pk(50));
}
__device__ __forceinline__ void store_q_t(const float (&a)[52], uint32_t addr, uint32_t addr_hi, uint32_t addr_last, int src) {
  auto pk = [&](int i) { return pack_bf16(a[i], a[i + 1]); };
#pragma unroll
  for (int w = 0; w < 4; w++) {
    stsm_x4_t(addr + kQOff + 2 * w * 1024, pk(12 * w), pk(12 * w + 2), pk(12 * w + 4), pk(12 * w + 6));
    if (w & 1) stsm_x4_t(addr_hi + kQOff + (6 + 2 * w) * 1024, pk(12 * w - 4), pk(12 * w - 2), pk(12 * w + 8), pk(12 * w + 10));
  }
  const uint32_t r0 = __shfl_sync(0xffffffffu, pk(48), src), r1 = __shfl_sync(0xffffffffu, pk(50), src);
  stsm_x4_t(addr_last, r0, r1, r0, r1);
  stsm_x4_t(addr_last ^ 0x240, r0, r1, r0, r1);
}

constexpr float kC = 0.125f * 1.4426950408889634f;

__device__ __forceinline__ float quad_sum(float t) {
  t += __shfl_xor_sync(0xffffffffu, t, 1);
  t += __shfl_xor_sync(0xffffffffu, t, 2);
  return t;
}
#define PIN(x) asm volatile("" : "+f"(x)::"memory")
struct Q3 { float t, s1, s2, s3; };
__device__ __forceinline__ Q3 q3_start(float t, int m) {
  Q3 q;
  q.t = t;
  q.s1 = __shfl_xor_sync(0xffffffffu, t, m);
  q.s2 = __shfl_xor_sync(0xffffffffu, t, 2 * m);
  q.s3 = __shfl_xor_sync(0xffffffffu, t, 3 * m);
  return q;
}
__device__ __forceinline__ float q3_end(const Q3& q) { return (q.t + q.s1) + (q.s2 + q.s3); }
template <bool TIGHT> __device__ __forceinline__ bool out_of_range(float t) {
  return TIGHT ? !(t >= 0x1p-7f && t <= 0x1p12f) : !(t >= 0x1p-30f && t <= 0x1p30f);
}

template <int O> __device__ __forceinline__ void set_exp(float (&s)[52], int j, float& t, bool tail_invalid) {
  s[4 * j + O] = ex2(s[4 * j + O]);
  s[4 * j + O + 1] = ex2(s[4 * j + O + 1]);
  if (j == 0) t = s[O] + s[O + 1];
  else if (j < 12 || !tail_invalid) { t += s[4 * j + O]; t += s[4 * j + O + 1]; }
}
template <int O, bool PACKED = true> __device__ __forceinline__ void norm_set(const float (&s)[52], int c, float iv, uint32_t paddr) {
  const int i = 16 * c + O;
  const uint32_t v2 = pack_bf16(iv, iv);
  auto pk = [&](int k) {
    if (!PACKED) return pack_bf16(s[k] * iv, s[k + 1] * iv);
    uint32_t r;
    asm("mul.rn.bf16x2 %0, %1, %2;\n" : "=r"(r) : "r"(pack_bf16(s[k], s[k + 1])), "r"(v2));
    return r;
  };
  if (c < 3) stsm_x4(paddr + 4 * c * kPL, pk(i), pk(i + 4), pk(i + 8), pk(i + 12));
  else stsm_x1(paddr + 12 * kPL, pk(48 + O));
}
template <int O> __device__ __forceinline__ void set_exact(float (&s)[52], uint32_t paddr, bool tail_invalid) {
  if (tail_invalid) { s[48 + O] = -INFINITY; s[49 + O] = -INFINITY; }
  float m = fmaxf(s[O], s[O + 1]);
#pragma unroll
  for (int j = 1; j < 13; j++) m = fmaxf(m, fmaxf(s[4 * j + O], s[4 * j + O + 1]));
  m = fmaxf(m, __shfl_xor_sync(0xffffffffu, m, 1));
  m = fmaxf(m, __shfl_xor_sync(0xffffffffu, m, 2));
  float t;
#pragma unroll
  for (int j = 0; j < 13; j++) {
    s[4 * j + O] -= m; s[4 * j + O + 1] -= m;
    set_exp<O>(s, j, t, tail_invalid);
  }
  const float iv = rcp(quad_sum(t));
#pragma unroll
  for (int c = 0; c < 4; c++) norm_set<O, false>(s, c, iv, paddr);
}

__device__ __forceinline__ void sched_barrier() { asm volatile("pmevent 1;\n" ::: "memory"); }

__device__ __forceinline__ void scale_wq(uint32_t (&w)[32]) {
#pragma unroll
  for (int i = 0; i < 32; i++)
    asm("{.reg .b32 t;\nmul.rn.bf16x2 t, %0, %2;\nfma.rn.bf16x2 %0, %0, %1, t;}\n" : "+r"(w[i]) : "r"(0x3e393e39u), "r"(0xb9acb9acu));
}
__device__ __forceinline__ void issue_s(float (&a)[52], uint64_t dq, uint64_t dk) {
#pragma unroll
  for (int s = 0; s < 4; s++) {
    if (s == 0) mma_ss_tied(a, dq, dk);
    else mma_ss(a, dq + 2 * s, dk + 2 * s);
  }
}
__device__ __forceinline__ void issue_pv(float (&a)[52], const uint32_t (&vf)[26], uint64_t dp, uint32_t z0 = 0, uint32_t z1 = 0) {
#pragma unroll
  for (int s = 0; s < 6; s++) mma_rs<true>(a, vf[4 * s], vf[4 * s + 1], vf[4 * s + 2], vf[4 * s + 3], dp + (kPL / 8) * s);
  mma_rs<true>(a, vf[24], vf[25], z0, z1, (dp + (kPL / 8) * 6) & ~((uint64_t)0x3FFF << 16));
}

__device__ __forceinline__ void exact_redo(const CUtensorMap* tm_e, const CUtensorMap* tm_o, const CUtensorMap* tm_q,
                                        const CUtensorMap* tm_k, const CUtensorMap* tm_v, int n_tiles) {
  constexpr uint32_t sbase = kS;
  auto zero = [&]() {
    uint32_t z;
    asm volatile("ld.volatile.shared.u32 %0, [%1];\n" : "=r"(z) : "r"(sbase + kF * 128) : "memory");
    return z;
  };
  const int tid = threadIdx.x + zero(), wg = tid >> 7, warp = (tid >> 5) & 3, lane = tid & 31;
  const int grid = gridDim.x - 2, cta = blockIdx.x - 2, head = wg ^ (cta & 1);
  const uint32_t wgb = sbase + kWGBase + wg * kWGRegion;
  const uint32_t bar_w = sbase + kBarOff + 64 + 32 * wg, bar_e = sbase + kBarOff + 128 + 8 * wg;
  const uint32_t flags = __ballot_sync(0xffffffffu, lds16(sbase + kBadOff + 32 * wg + (lane & ~1)) >> (8 * (lane & 1)) & 255);
  const int n_iter = wg == 0 ? max(n_tiles, lds(sbase + kOpenOff)) : n_tiles;
  const bool elected = warp == kElect && lane == 0;
  const bool tail_invalid = (lane & 2) != 0;
  const uint32_t t_addr = wgb + ((lane >> 4) * 8 + (lane & 7)) * 128 + (((2 * warp + ((lane >> 3) & 1)) ^ (lane & 7)) << 4);
  const uint32_t q12_k = (2 * (lane >> 4) + ((lane >> 2) & 1) + 2 * (lane & 3)) & 7;
  uint32_t q12_addr = wgb + kQOff + (9 + 2 * (lane & 3)) * 1024 + q12_k * 128 + (((2 * warp + ((lane >> 3) & 1)) ^ q12_k) << 4);
  const uint32_t p8_addr = wgb + kPOff + lane * 16 + (kPL - 128) / 8 * (lane & 24);
  auto e_desc = [&](int st) { return desc_sw128(sbase + (st + wg + zero()) * kEStage); };
  auto g_addr = [&]() { return wgb + zero(); };

  if (elected) {
    asm volatile("cp.async.bulk.wait_group 0;\n" ::: "memory");
    mbar_expect_tx(bar_w, 3 * 16384);
    tma_load_2d(wgb, tm_q, 0, head * 128, bar_w);
    tma_load_2d(wgb + 16384, tm_k, 0, head * 128, bar_w);
    tma_load_2d(sbase + (2 + wg) * kEStage, tm_v, 0, head * 128, bar_w);
  }
  mbar_wait(bar_w, 1);
  uint32_t wQ[32], wK[32], vf[26];
#pragma unroll
  for (int s = 0; s < 8; s++) {
    ldsm_x4_t(t_addr + s * 2048, wQ[4 * s], wQ[4 * s + 1], wQ[4 * s + 2], wQ[4 * s + 3]);
    ldsm_x4_t(t_addr + 16384 + s * 2048, wK[4 * s], wK[4 * s + 1], wK[4 * s + 2], wK[4 * s + 3]);
  }
  scale_wq(wQ);
  auto publish = [&]() {
    bar_sync(1 + wg, 128);
    fence_async();
  };
  bar_sync(1 + wg, 128);
  float acc1[52], acc2[52];
  uint32_t ph = 0;
  for (int t = 0; t < n_iter; t++) {
    if (!__any_sync(0xffffffffu, (flags >> min(t, 31)) & 1)) continue;
    const int row = t == n_tiles ? lds(sbase + kOpenOff + 4) : (t * grid + (t == 0 ? cta ^ head : cta)) * kF;
    if (elected) {
      mbar_expect_tx(bar_e, kETx);
      tma_load_2d(sbase + wg * kEStage, tm_e, 0, row, bar_e);
      tma_load_2d(sbase + wg * kEStage + kEHalf, tm_e, 64, row, bar_e);
    }
    mbar_wait(bar_e, ph);
    ph ^= 1;
    {
      const uint64_t dE = e_desc(0);
      wg_fence();
      proj(acc2, wQ, dE);
      proj(acc1, wK, dE);
      wg_commit();
    }
    wg_wait<0>();
    fence_acc(acc1);
    fence_acc(acc2);
    store_q_t(acc2, t_addr, t_addr + (lane >> 4) * 1024, q12_addr, lane & 29);
    store_t<false>(acc1, t_addr + kKOff);
    {
      const uint64_t dE = e_desc(0), dWv = e_desc(2);
      wg_fence();
      proj_r<false, false>(acc2, nullptr, dE, dWv);
      wg_commit();
    }
    wg_wait<0>();
    fence_acc(acc2);
#pragma unroll
    for (int i = 0; i < 26; i++) vf[i] = pack_bf16(acc2[2 * i], acc2[2 * i + 1]);
    publish();
    {
      const uint32_t g = g_addr();
      const uint64_t dQ = desc_sw128(g + kQOff), dK = desc_sw128(g + kKOff);
      wg_fence();
      issue_s(acc1, dQ, dK);
      issue_s(acc2, dQ + 512, dK);
      wg_commit();
    }
    wg_wait<0>();
    fence_acc(acc1);
    fence_acc(acc2);
    bar_sync(1 + wg, 128);
    set_exact<0>(acc1, p8_addr + 3 * warp * kPGrp, tail_invalid);
    set_exact<2>(acc1, p8_addr + (3 * warp + 1) * kPGrp, tail_invalid);
    set_exact<0>(acc2, p8_addr + (3 * warp + 2) * kPGrp, tail_invalid);
    set_exact<2>(acc2, wgb + kPOff + 12 * kPGrp + (lane >> 3) * kPL + warp * 16, tail_invalid);
    publish();
    {
      const uint32_t g = g_addr();
      const uint64_t dE = e_desc(0), dW = desc_sw128(g + kWsOff), dP = desc_p(g + kPOff);
      wg_fence();
      proj_r<false, false>(acc1, nullptr, dE, dW);
      issue_pv(acc1, vf, dP);
      wg_commit();
    }
    wg_wait<0>();
    fence_acc(acc1);
    store_t<true>(acc1, t_addr + kOOff);
    publish();
    if (elected) {
      tma_store_2d(tm_o, wgb + kOOff, head * 64, row);
      asm volatile("cp.async.bulk.commit_group;\n" ::: "memory");
      asm volatile("cp.async.bulk.wait_group 0;\n" ::: "memory");
    }
    bar_sync(1 + wg, 128);
  }
}

#define D32_REGS "{%0,%1,%2,%3,%4,%5,%6,%7,%8,%9,%10,%11,%12,%13,%14,%15,%16,%17,%18,%19,%20,%21,%22,%23,%24,%25,%26,%27,%28,%29,%30,%31}"
#define D32_OPS(c, d)                                                                                        \
  c(d[0]), c(d[1]), c(d[2]), c(d[3]), c(d[4]), c(d[5]), c(d[6]), c(d[7]), c(d[8]), c(d[9]), c(d[10]),        \
  c(d[11]), c(d[12]), c(d[13]), c(d[14]), c(d[15]), c(d[16]), c(d[17]), c(d[18]), c(d[19]), c(d[20]),        \
  c(d[21]), c(d[22]), c(d[23]), c(d[24]), c(d[25]), c(d[26]), c(d[27]), c(d[28]), c(d[29]), c(d[30]), c(d[31])
template <int ACC, int SA, int T>
__device__ __forceinline__ void mma64_ss(float (&d)[32], uint64_t da, uint64_t db) {
  if constexpr (ACC)
    asm volatile("wgmma.mma_async.sync.aligned.m64n64k16.f32.bf16.bf16 " D32_REGS ", %32, %33, 1, %34, 1, %35, %35;\n"
                 : D32_OPS("+f", d) : "l"(da), "l"(db), "n"(SA), "n"(T));
  else
    asm volatile("wgmma.mma_async.sync.aligned.m64n64k16.f32.bf16.bf16 " D32_REGS ", %32, %33, 0, %34, 1, %35, %35;\n"
                 : D32_OPS("=f", d) : "l"(da), "l"(db), "n"(SA), "n"(T));
}
template <int ACC, int T>
__device__ __forceinline__ void mma64_rs(float (&d)[32], const uint32_t* a, uint64_t db) {
  if constexpr (ACC)
    asm volatile("wgmma.mma_async.sync.aligned.m64n64k16.f32.bf16.bf16 " D32_REGS ", {%32,%33,%34,%35}, %36, 1, 1, 1, %37;\n"
                 : D32_OPS("+f", d) : "r"(a[0]), "r"(a[1]), "r"(a[2]), "r"(a[3]), "l"(db), "n"(T));
  else
    asm volatile("wgmma.mma_async.sync.aligned.m64n64k16.f32.bf16.bf16 " D32_REGS ", {%32,%33,%34,%35}, %36, 0, 1, 1, %37;\n"
                 : D32_OPS("=f", d) : "r"(a[0]), "r"(a[1]), "r"(a[2]), "r"(a[3]), "l"(db), "n"(T));
}
__device__ __forceinline__ void mma64_done(float (&d)[32]) {
  wg_commit();
  wg_wait<0>();
  asm volatile("" : D32_OPS("+f", d)::"memory");
}
__device__ __forceinline__ float bf_lo(uint32_t x) { return __uint_as_float(x << 16); }
__device__ __forceinline__ float bf_hi(uint32_t x) { return __uint_as_float(x & 0xffff0000u); }
__device__ __forceinline__ void split2(float x, float y, uint32_t& hi, uint32_t& lo) {
  hi = pack_bf16(x, y);
  lo = pack_bf16(x - bf_lo(hi), y - bf_hi(hi));
}
__device__ __forceinline__ float ldsf(uint32_t a) { return __int_as_float(lds(a)); }
__device__ __forceinline__ float2 ldsf2(uint32_t a) {
  float2 v;
  asm volatile("ld.shared.v2.f32 {%0,%1}, [%2];\n" : "=f"(v.x), "=f"(v.y) : "r"(a) : "memory");
  return v;
}
__device__ __forceinline__ float4 ldsf4(uint32_t a) {
  float4 v;
  asm volatile("ld.shared.v4.f32 {%0,%1,%2,%3}, [%4];\n" : "=f"(v.x), "=f"(v.y), "=f"(v.z), "=f"(v.w) : "r"(a) : "memory");
  return v;
}
__device__ __forceinline__ void stsf2(uint32_t a, float x, float y) { asm volatile("st.shared.v2.f32 [%0], {%1,%2};\n" ::"r"(a), "f"(x), "f"(y) : "memory"); }
__device__ __forceinline__ void stsf4(uint32_t a, float x, float y, float z, float w) {
  asm volatile("st.shared.v4.f32 [%0], {%1,%2,%3,%4};\n" ::"r"(a), "f"(x), "f"(y), "f"(z), "f"(w) : "memory");
}
__device__ __forceinline__ float tf_lo(float x) { return x - __uint_as_float(__float_as_uint(x) & 0xffffe000u); }
__device__ __forceinline__ void mma_tf32(float* c, float a0, float a1, float a2, float a3, float b0, float b1) {
  asm("mma.sync.aligned.m16n8k8.row.col.f32.tf32.tf32.f32 {%0,%1,%2,%3}, {%4,%5,%6,%7}, {%8,%9}, {%0,%1,%2,%3};\n"
      : "+f"(c[0]), "+f"(c[1]), "+f"(c[2]), "+f"(c[3])
      : "r"(__float_as_uint(a0)), "r"(__float_as_uint(a1)), "r"(__float_as_uint(a2)), "r"(__float_as_uint(a3)), "r"(__float_as_uint(b0)), "r"(__float_as_uint(b1)));
}
__device__ __forceinline__ float warp_sum(float t) {
#pragma unroll
  for (int m = 1; m < 32; m *= 2) t += __shfl_xor_sync(0xffffffffu, t, m);
  return t;
}

__device__ __forceinline__ void transform_weights(int z, int warp) {
  unsigned epoch = 0;
  if (threadIdx.x == 192) epoch = *(volatile unsigned*)&g_epoch;
  const int t = threadIdx.x & 127, lane = t & 31, q = lane & 3, r = 16 * warp + (lane >> 2);
  constexpr uint32_t kWq = kS + kWGBase, kWk = kWq + 16384, kWv = kS + kEStage;
  auto tile_hi = [](int s) { return kS + kWGBase + s * kWGRegion + 32768; };
  auto tile_lo = [](int s) { return kS + (1 + s) * kEStage + 16384; };
  const uint32_t tX = z ? kWv : kWq, tH = tile_hi(z), tL = tile_lo(z);
  const uint32_t big = kS + kWGBase + kWGRegion + z * 16384, gt = kS + z * kEHalf;
  const uint32_t n2 = kS + kTmpOff + z * 1024, buf = kS + 2 * kEStage + z * 8192;
  uint4* dst = &g_w[blockIdx.x][0][t] + (8 * z - 3) * 128;
  auto store_big = [&](const float (&d)[32]) {
#pragma unroll
    for (int g = 0; g < 8; g++) {
      const uint32_t a = big + r * 256 + ((g ^ (lane >> 2)) << 5) + 8 * q;
      stsf2(a, d[4 * g], d[4 * g + 1]);
      stsf2(a + 2048, d[4 * g + 2], d[4 * g + 3]);
    }
  };
#pragma unroll 1
  for (int i = 0; i < 5; i++) sts4(gt + 16 * t + 2048 * i, 0, 0, 0, 0);
  mbar_wait(kS + kBarOff + 64 + 16 * z, 0);
  float d[32];
  wg_fence();
#pragma unroll
  for (int s = 0; s < 4; s++) {
    if (s == 0) mma64_ss<0, 1, 0>(d, desc_sw128(tX - 2048 * z), desc_sw128(tX));
    else mma64_ss<1, 1, 0>(d, desc_sw128(tX - 2048 * z) + 2 * s, desc_sw128(tX) + 2 * s);
  }
  mma64_done(d);
  bool ok = true;
  uint32_t fh[16], fl[16];
  auto split_d = [&](int n) {
#pragma unroll
    for (int i = 0; i < n; i++) split2(d[2 * i], d[2 * i + 1], fh[i], fl[i]);
  };
  const int wr = warp - z, c8 = lane >> 2;
  if ((unsigned)wr < 3) {
    const bool dg = c8 >> 1 == q, odd = c8 & 1;
    if (dg) {
      const float x0 = odd ? d[1] : d[0], x1 = odd ? d[9] : d[8], x2 = odd ? d[17] : d[16];
      const float y0 = odd ? d[7] : d[6], y1 = odd ? d[15] : d[14], y2 = odd ? d[23] : d[22];
      sts(n2 + 512 + 64 * wr + 4 * c8, __float_as_int(rsq(wr == 0 ? x0 : wr == 1 ? x1 : x2)));
      sts(n2 + 544 + 64 * wr + 4 * c8, __float_as_int(rsq(wr == 0 ? y0 : wr == 1 ? y1 : y2)));
    }
    bar_sync(8 + z, 96);
    const float r0 = ldsf(n2 + 512 + 64 * wr + 4 * c8), r1 = ldsf(n2 + 544 + 64 * wr + 4 * c8);
    auto scale = [&](float a, float b) {
#pragma unroll
      for (int g = 0; g < 6; g++) {
        const float2 c = ldsf2(n2 + 512 + 32 * g + 8 * q);
        d[4 * g] *= a * c.x; d[4 * g + 1] *= a * c.y; d[4 * g + 2] *= b * c.x; d[4 * g + 3] *= b * c.y;
      }
    };
    scale(r0, r1);
    const float fe = dg && !odd, fo = dg && odd;
    const uint32_t lo_mask = q < 2 ? 0u : 0xffffe000u;
    const bool e = q & 1;
#pragma unroll 1
    for (int k = 0; k < 3; k++) {
      float x[8], m[8];
      const float ge = wr == k ? fe : 0.f, go = wr == k ? fo : 0.f;
#pragma unroll
      for (int i = 0; i < 8; i++) m[i] = d[i];
      d[0] -= ge; d[1] -= go; d[6] -= ge; d[7] -= go;
      const uint32_t xb = buf + 4096 * (k & 1) + 1024 * (wr - k < 0 ? wr - k + 3 : wr - k) + 16 * lane;
      stsf4(xb, d[0], d[1], d[4], d[5]);
      stsf4(xb + 512, d[2], d[3], d[6], d[7]);
#pragma unroll
      for (int i = 0; i < 8; i++) x[i] = d[i];
      d[0] -= ge; d[1] -= go; d[6] -= ge; d[7] -= go;
      if (wr == k) {
#pragma unroll
        for (int h = 0; h < 2; h++) {
#pragma unroll 1
          for (int p = 0; p < 4; p++) {
            const float ie = q == p ? fe : 0.f, io = q == p ? fo : 0.f;
            const float px = __shfl_sync(0xffffffffu, m[6 * h], 9 * p), py = __shfl_sync(0xffffffffu, m[6 * h + 1], 9 * p);
            const float pw = __shfl_sync(0xffffffffu, m[6 * h + 1], 9 * p + 4);
            m[6 * h] -= ie; m[6 * h + 1] -= io;
            float y[4];
#pragma unroll
            for (int i = 0; i < 4; i++) y[i] = __shfl_sync(0xffffffffu, m[4 * h + i], p, 4);
            m[6 * h] -= ie; m[6 * h + 1] -= io;
            const float id = rcp(px * pw - py * py), po = e ? px : pw;
            const float o0 = e ? y[1] : y[0], s0 = e ? y[0] : y[1], o1 = e ? y[3] : y[2], s1 = e ? y[2] : y[3];
            const float w0 = (s0 * py - o0 * po) * id, w1 = (s1 * py - o1 * po) * id;
            const float b0 = o0 - __uint_as_float(__float_as_uint(o0) & lo_mask), b1 = o1 - __uint_as_float(__float_as_uint(o1) & lo_mask);
            mma_tf32(m, w0, w1, tf_lo(w0), tf_lo(w1), b0, b0);
            mma_tf32(m + 4, w0, w1, tf_lo(w0), tf_lo(w1), b1, b1);
          }
        }
        stsf4(buf + 4096 * (k & 1) + 3072 + 16 * lane, m[0], m[1], m[4], m[5]);
        stsf4(buf + 4096 * (k & 1) + 3584 + 16 * lane, m[2], m[3], m[6], m[7]);
      }
      bar_sync(8 + z, 96);
      auto mul = [&](auto c0, auto c1, int n, const float (&a)[8], const float4* b) {
        float l[8];
#pragma unroll
        for (int i = 0; i < 8; i++) l[i] = tf_lo(a[i]);
#pragma unroll
        for (int t = 0; t < 3; t++) {
          const float* u = t == 1 ? l : a;
#pragma unroll
          for (int j = 0; j < n; j++) mma_tf32(c0(j), u[0], u[2], u[1], u[3], t == 2 ? tf_lo(b[j].x) : b[j].x, t == 2 ? tf_lo(b[j].y) : b[j].y);
#pragma unroll
          for (int j = 0; j < n; j++) mma_tf32(c1(j), u[4], u[6], u[5], u[7], t == 2 ? tf_lo(b[j].z) : b[j].z, t == 2 ? tf_lo(b[j].w) : b[j].w);
        }
      };
      float4 b[8];
#pragma unroll
      for (int j = 0; j < 8; j++) b[(j + 6) % 8] = ldsf4(buf + 4096 * (k & 1) + 512 * ((j + 6) % 8) + 16 * lane);
      float m2[8];
#pragma unroll
      for (int i = 0; i < 8; i++) m[i] = m2[i] = 0.f;
      mul([&](int j) { return m + 4 * j; }, [&](int j) { return m2 + 4 * j; }, 2, x, b + 6);
#pragma unroll
      for (int i = 0; i < 8; i++) m[i] += m2[i];
      mul([&](int j) { return d + 4 * j; }, [&](int j) { return d + 4 * j; }, 6, m, b);
#pragma unroll
      for (int i = 0; i < 8; i++) { const float v = d[i]; d[i] = d[8 + i]; d[8 + i] = d[16 + i]; d[16 + i] = v; }
    }
#pragma unroll
    for (int i = 0; i < 24; i++) ok &= fabsf(d[i]) <= 32.f;
    scale(-r0, -r1);
  }
  split_d(12);
  wg_fence();
#pragma unroll
  for (int s = 0; s < 3; s++) {
    if (s == 0) mma64_rs<0, 1>(d, fh, desc_sw128(tX));
    else mma64_rs<1, 1>(d, fh + 4 * s, desc_sw128(tX) + 128 * s);
    mma64_rs<1, 1>(d, fl + 4 * s, desc_sw128(tX) + 128 * s);
  }
  mma64_done(d);
  split_d(16);
#pragma unroll
  for (int g = 0; g < 4; g++) {
    const uint32_t c = (16 * (wr & 3) + (lane & 15)) * 128 + (((2 * g + (lane >> 4)) ^ (lane & 7)) << 4);
    stsm_x4(tH + c, fh[4 * g], fh[4 * g + 1], fh[4 * g + 2], fh[4 * g + 3]);
    stsm_x4(tL + c, fl[4 * g], fl[4 * g + 1], fl[4 * g + 2], fl[4 * g + 3]);
  }
  mbar_wait(kS + kBarOff + 64 + 8, 0);
  mbar_wait(kS + kBarOff + 64 + 16 - 16 * z, 0);
  fence_async();
  bar_sync(1 + z, 128);
  wg_fence();
#pragma unroll
  for (int s = 0; s < 3; s++) {
    if (s == 0) mma64_ss<0, -1, 1>(d, desc_sw128(tX), desc_sw128(tH));
    else mma64_ss<1, -1, 1>(d, desc_sw128(tX) + 128 * s, desc_sw128(tH) + 128 * s);
    mma64_ss<1, -1, 1>(d, desc_sw128(tX) + 128 * s, desc_sw128(tL) + 128 * s);
  }
  mma64_done(d);
  store_big(d);
  float dm[32];
  auto mm = [&](uint32_t x, uint32_t y, bool first) {
    const uint64_t da = desc_sw128(z ? y : x), db = desc_sw128(z ? x : y);
    if (first) mma64_ss<0, 1, 1>(dm, da, db); else mma64_ss<1, 1, 1>(dm, da, db);
  };
  wg_fence();
#pragma unroll
  for (int s = 0; s < 3; s++) { mm(kWq + kWv - tX + 2048 * s, tH + 2048 * s, s == 0); mm(kWq + kWv - tX + 2048 * s, tL + 2048 * s, false); }
  wg_commit();
  bar_sync(1 + z, 128);
  if (warp == z) {
    const uint32_t da = big + lane * 512 + ((8 * lane) ^ ((lane & 3) << 6)), db = (da ^ 32) + 260;
    float dx = ldsf(da) + 1.f, dy = ldsf(db) + 1.f;
    sts(da, __float_as_int(dx));
    sts(db, __float_as_int(dy));
    float hx[16], hy[16];
#pragma unroll
    for (int i = 0; i < 16; i++) hx[i] = hy[i] = 0.f;
#pragma unroll 1
    for (int c = 0; c < 16; c += 4) {
#pragma unroll
      for (int e = 3; e >= 0; e--) {
        __syncwarp();
        const int key = __reduce_max_sync(0xffffffffu, max((__float_as_int(dx) & ~63) | (2 * lane), (__float_as_int(dy) & ~63) | (2 * lane + 1)));
        const int p = key & 63;
        const float2 row = ldsf2(big + p * 256 + ((8 * lane) ^ ((p & 7) << 5)));
        float k[16];
#pragma unroll
        for (int i = e == 3; i < 4; i++) {
          const float4 v = ldsf4(gt + p * 144 + 48 - 4 * c + 16 * i);
          k[4 * i] = v.x; k[4 * i + 1] = v.y; k[4 * i + 2] = v.z; k[4 * i + 3] = v.w;
        }
        const float is = rsq(__int_as_float(key));
        float ux[4] = {row.x, 0.f, 0.f, 0.f}, uy[4] = {row.y, 0.f, 0.f, 0.f};
#pragma unroll
        for (int i = e + 1; i < 16; i++) { ux[i >> 2] = fmaf(-k[i], hx[i], ux[i >> 2]); uy[i >> 2] = fmaf(-k[i], hy[i], uy[i >> 2]); }
        hx[e] = ((ux[0] + ux[1]) + (ux[2] + ux[3])) * is;
        hy[e] = ((uy[0] + uy[1]) + (uy[2] + uy[3])) * is;
        dx = fmaf(-hx[e], hx[e], dx);
        dy = fmaf(-hy[e], hy[e], dy);
        sts(gt + lane * 288 + 48 - 4 * c + 4 * e, __float_as_int(hx[e]));
        sts(gt + lane * 288 + 192 - 4 * c + 4 * e, __float_as_int(hy[e]));
        ok &= key >= 0x3c000000;
      }
#pragma unroll
      for (int i = 15; i >= 4; i--) { hx[i] = hx[i - 4]; hy[i] = hy[i - 4]; }
    }
    ok &= fmaxf(fabsf(dx), fabsf(dy)) <= 0x1p-10f;
  } else if (warp >= 2) {
#pragma unroll 1
    for (int h = 0; h < 2; h++) {
      const int row = (t & 63) + 64 * h;
      float a = 0.f, b = 0.f;
#pragma unroll 2
      for (int c = 0; c < 8; c++) {
        const int4 v = lds4(tX + row * 128 + ((c ^ (t & 7)) << 4));
        const uint32_t w[4] = {(uint32_t)v.x, (uint32_t)v.y, (uint32_t)v.z, (uint32_t)v.w};
#pragma unroll
        for (int k = 0; k < 4; k++) { a = fmaf(bf_lo(w[k]), bf_lo(w[k]), a); b = fmaf(bf_hi(w[k]), bf_hi(w[k]), b); }
      }
      sts(n2 + 4 * row, __float_as_int(a + b));
    }
    bar_sync(8 + z, 64);
    const float s = warp_sum(ldsf(n2 + 4 * lane) + (lane < 16 ? ldsf(n2 + 128 + 4 * lane) : 0.f)) * (1.f / 48);
    if (t == 64) sts(n2 + 1020, __float_as_int(s));
  }
  bar_sync(1 + z, 128);
  const float s2 = ldsf(n2 + 1020);
  ok &= (s2 >= 0x1p-60f) & (s2 <= 0x1p60f);
  {
    const float4 gx = ldsf4(gt + lane * 288 + 16 * warp), gy = ldsf4(gt + lane * 288 + 144 + 16 * warp);
    const float vx[4] = {gx.x, gx.y, gx.z, gx.w}, vy[4] = {gy.x, gy.y, gy.z, gy.w};
    float k = rsq(s2);
#pragma unroll 1
    for (int h = 0; h < 2; h++) {
#pragma unroll
      for (int i = 0; i < 4; i++) {
        uint32_t hi, lo;
        const uint32_t o = 6144 + 2048 * h + (4 * warp + i) * 128 + ((4 * lane) ^ (((4 * warp + i) & 7) << 4));
        split2(vx[i] * k, vy[i] * k, hi, lo);
        sts(tH + o, hi);
        sts(tL + o, lo);
      }
      k *= s2;
    }
  }
  fence_async();
  __syncthreads();
  wg_fence();
  mm(tile_hi(1 - z) + 8192, tH + 6144, false); mm(tile_hi(1 - z) + 8192, tL + 6144, false); mm(tile_lo(1 - z) + 8192, tH + 6144, false);
  wg_commit();
  const float so = ldsf(kS + kTmpOff + (1 - z) * 1024 + 1020);
  ok &= z | (ldsf(kS + kTmpOff + 4 * t) * so <= 6.f * s2 * ldsf(kS + kTmpOff + 1024 + 4 * t));
  wg_wait<0>();
  asm volatile("" : D32_OPS("+f", dm)::"memory");
  float nn = 0.f;
#pragma unroll
  for (int i = 0; i < 32; i++) { nn = fmaf(dm[i], dm[i], nn); d[i] = dm[i] * (z ? kC : 1.f); }
  split_d(16);
  {
    const uint64_t db = desc_sw128(z ? kWk : kWq);
    float d2[32];
    wg_fence();
#pragma unroll
    for (int s = 0; s < 4; s++) {
      if (s == 0) mma64_rs<0, 0>(d2, fh, db + 512); else mma64_rs<1, 0>(d2, fh + 4 * s, db + 512 + 2 * s);
      mma64_rs<1, 0>(d2, fl + 4 * s, db + 512 + 2 * s);
    }
    wg_commit();
#pragma unroll
    for (int s = 0; s < 4; s++) {
      if (s == 0) mma64_rs<0, 0>(d, fh, db); else mma64_rs<1, 0>(d, fh + 4 * s, db + 2 * s);
      mma64_rs<1, 0>(d, fl + 4 * s, db + 2 * s);
    }
    wg_commit();
    ok &= warp_sum(nn) * s2 <= 128.f * so;
    auto out = [&](const float* x, int s) {
      if (s >= 3 || z) dst[s * 128] = make_uint4(pack_bf16(x[0], x[1]), pack_bf16(x[2], x[3]), pack_bf16(x[4], x[5]), pack_bf16(x[6], x[7]));
    };
    wg_wait<1>();
    asm volatile("" : D32_OPS("+f", d2)::"memory");
#pragma unroll
    for (int s = 0; s < 4; s++) out(d2 + 8 * s, 4 + s);
    wg_wait<0>();
    asm volatile("" : D32_OPS("+f", d)::"memory");
#pragma unroll
    for (int s = 0; s < 4; s++) out(d + 8 * s, s);
  }
  const int all = __syncthreads_and(ok);
  if (threadIdx.x == 192) {
    asm volatile("st.release.gpu.global.u32 [%0], %1;\n" ::"l"(g_state + blockIdx.x), "r"(2 * epoch + 2 + (all != 0)) : "memory");
    if (atomicInc(&g_seen, gridDim.x - 1) == gridDim.x - 1) g_epoch = epoch + 1;
  }
}

template <int V> struct IC { __device__ constexpr operator int() const { return V; } };
struct WPtrs { const uint8_t* p[4]; };

__global__ void __launch_bounds__(256, 1)
autoint_kernel(const __grid_constant__ CUtensorMap tm_e, const __grid_constant__ CUtensorMap tm_o,
               const __grid_constant__ CUtensorMap tm_q, const __grid_constant__ CUtensorMap tm_k,
               const __grid_constant__ CUtensorMap tm_v, const __grid_constant__ CUtensorMap tm_r,
               const uint8_t* p_e, const __grid_constant__ WPtrs pw,
               const int grid, const int n_base, const int n_extra, const int n_skip, const int zero, const int n_open) {
  extern __shared__ __align__(1024) uint8_t smem[];
  const int tid = threadIdx.x;
  if ((tid & 31) == 0 && tid >= 64) asm volatile("prefetch.tensormap [%0];\n" ::"l"((const char*)&tm_e + (tid - 64) * 4) : "memory");
  if (tid < 200) asm volatile("prefetch.global.L2 [%0];\n" ::"l"(p_e + max(((int)blockIdx.x & ~1) - 2, 0) * (kF * kD * 2) + tid * 128) : "memory");
  else if (tid < 208) asm volatile("prefetch.global.L2 [%0];\n" ::"l"(pw.p[(blockIdx.x >> 5) & 3] + (blockIdx.x & 31) * 1024 + (tid & 7) * 128) : "memory");
  constexpr uint32_t bar_full = kS + kBarOff;
  constexpr uint32_t bar_w = kS + kBarOff + 64;
  const int cta = blockIdx.x - 2;
  const int n_tiles = n_base + (cta < n_extra) - (cta >= grid - 2 ? n_skip : 0);
  auto row_of = [&](int t) { return (t * grid + cta) * kF; };
  auto load_r = [&](int row, int st, uint32_t bar) {
    mbar_expect_tx(bar, kETx);
    tma_load_2d_stream(kS + st * kEStage, &tm_e, 0, row, bar);
    tma_load_2d_stream(kS + st * kEStage + kEHalf, &tm_e, 64, row, bar);
  };

  auto load_w = [&](int w, int m) {
    const int h = w ^ (cta & 1);
    const uint32_t dst = kS + kWGBase + w * kWGRegion, bar = bar_w + 8 * (4 * w + m);
    mbar_expect_tx(bar, 16384);
    if (m == 0) tma_load_2d(dst, &tm_q, 0, h * 128, bar);
    if (m == 1) tma_load_2d(dst + 16384, &tm_k, 0, h * 128, bar);
    if (m == 2) tma_load_2d(kS + (1 + w) * kEStage, &tm_v, 0, h * 128, bar);
    if (m == 3) tma_load_2d(dst + kWsOff, &tm_r, h * 64, 0, bar);
  };
  if (tid == 0) {
    mbar_init(bar_w + 80, 1);
    mbar_init(bar_w, 1);
    mbar_init(bar_w + 8, 1);
    mbar_init(bar_w + 16, 1);
    asm volatile("fence.mbarrier_init.release.cluster;\n" ::: "memory");
    fence_async();
    load_w(0, 0); load_w(0, 1); load_w(0, 2);
    if (cta >= 0) load_r((cta & ~1) * kF, 3, bar_w + 80);
  } else if (tid == 32) {
    if (smem_u32(smem) != kS) __trap();
    for (int s = 0; s < kStages; s++) mbar_init(bar_full + 8 * s, 1);
    for (int s = 3; s < 10; s++) mbar_init(bar_w + 8 * s, 1);
    for (int s = 0; s < 2; s++) mbar_init(bar_full + 32 + 8 * s, 1);
    asm volatile("fence.mbarrier_init.release.cluster;\n" ::: "memory");
  }
  const int wg_r = __shfl_sync(0xffffffffu, tid >> 7, 0);
  const int warp = __shfl_sync(0xffffffffu, (tid >> 5) & 3, 0);
  const int lane = tid & 31;
  auto st_zero = [&](uint32_t a) { asm volatile("st.shared.v4.u32 [%0], {%1,%1,%1,%1};\n" ::"r"(a), "r"(0) : "memory"); };
  if (tid >= 128) st_zero(kS + (warp + (warp & 2) * 2) * kEHalf + kF * 128 + lane * 16);
  fence_async();
  __syncthreads();
  if (blockIdx.x < 2) {
    transform_weights(wg_r, warp);
    if (zero == 0) return;
  } else {
    if (tid == 128) {
      load_w(1, 0); load_w(1, 1); load_w(1, 2); load_w(0, 3);
      load_r((cta | 1) * kF, 0, bar_full);
      load_w(1, 3);
    }
    if (tid >= 224 && tid < 228) sts4(kS + kBadOff + 16 * (tid - 224), 0, 0, 0, 0);
    if (tid == 160) {
      const int mod = max(n_open, 1), x = (cta >> 1) % mod, y = x - (n_open - 2 * n_skip);
      sts(kS + kOpenOff, 0);
      sts(kS + kOpenOff + 4, (n_open == 0 ? kB : y < 0 ? n_base * grid + x : (n_base - (y >> 1)) * grid - 2 + (y & 1)) * kF);
      const uint64_t ga = (uint64_t)__cvta_generic_to_global(g_claim + 2 * x + (cta & 1));
      sts4(kS + kClaimOff, (int)ga, (int)(ga >> 32), ((grid >> 1) - 1 - x) / mod, n_open ? n_tiles + 1 : 0);
    }
    if (tid == 192) sts(kS + kOpenOff + 8, 2 * *(volatile unsigned*)&g_epoch + 2);

    int it = -1;
    bool fast = false;
    uint32_t ln = lane;
    uint32_t wQ[32], wK[32], wV[32], vf[26];
    float acc1[52], acc2[52];
    uint32_t z0 = 0, z1 = 0;
    uint32_t t_addr = kS + kWGBase + (tid >> 7) * kWGRegion + ((lane >> 4) * 8 + (lane & 7)) * 128 + (((2 * warp + ((lane >> 3) & 1)) ^ (lane & 7)) << 4);
    const uint32_t q12_k = (2 * (lane >> 4) + ((lane >> 2) & 1) + 2 * (lane & 3)) & 7;
    uint32_t q12_addr = kS + kWGBase + (tid >> 7) * kWGRegion + kQOff + (9 + 2 * (lane & 3)) * 1024 + q12_k * 128 + (((2 * warp + ((lane >> 3) & 1)) ^ q12_k) << 4);
    asm volatile("xor.b32 %0, %0, %2;\nxor.b32 %1, %1, %2;\n" : "+r"(t_addr), "+r"(q12_addr) : "r"(zero));
    auto tail_inv = [&]() { return (ln & 2) != 0; };
    auto publish = [&](int wg) {
      bar_sync(1 + wg, 128);
      fence_async();
    };
    auto tma_out = [&](int wg, int row) {
      tma_store_2d(&tm_o, kS + kWGBase + wg * kWGRegion + kOOff, (wg ^ (cta & 1)) * 64, row);
      asm volatile("cp.async.bulk.commit_group;\n" ::: "memory");
    };

    auto iter = [&](auto wgc, auto fastc) __attribute__((always_inline)) {
      constexpr bool FAST = fastc;
      constexpr int wg = wgc;
      constexpr int kLag = 3, kRJ = FAST ? 9 : 11;
      constexpr uint32_t wgb = kS + kWGBase + wg * kWGRegion, bar_peek = bar_full + 32 + 8 * wg;
      const uint64_t dQ = desc_sw128(wgb + kQOff), dK = desc_sw128(wgb + kKOff), dP = desc_p(wgb + kPOff), dW = desc_sw128(wgb + kWsOff);
      auto p8_addr = [&]() { return wgb + kPOff + 3 * warp * kPGrp + ln * 16 + (kPL - 128) / 8 * (ln & 24); };
      auto cvt_v = [&]() {
#pragma unroll
        for (int i = 0; i < 26; i++) vf[i] = pack_bf16(acc2[2 * i], acc2[2 * i + 1]);
        asm volatile("and.b32 %0, %2, %3;\nand.b32 %1, %4, %3;\n" : "=r"(z0), "=r"(z1) : "r"(vf[0]), "r"(zero), "r"(vf[1]));
      };
      it++;
      const bool change = !FAST && it == (cta >= grid - 2 ? 1 : kSwitch);
      const bool own = !FAST && wg == 0 && it == 0;
      const int stage = own ? 3 : it & 3;
      const uint64_t dE = desc_sw128(kS) + (uint64_t)((stage * kEStage) >> 4);
      if (FAST || it > 0) {
        wg_fence();
        issue_pv(acc1, vf, dP, z0, z1);
        wg_commit();
      }
      mbar_wait(own ? bar_w + 80 : bar_full + 8 * stage, (it >> 2) & 1);
      wg_fence();
      proj(acc2, wQ, dE);
      wg_commit();
      if (wg == 1 && warp == kRefill && ln == 0 && (FAST || it >= 1) && it + kStages - 2 < n_tiles) {
        const int ps = (it - 1) & (kStages - 1);
        if (!FAST && it == 1) load_r(row_of(3), 3, bar_full + 24);
        load_r(it + kStages - 1 < n_tiles ? row_of(it + kStages - 1) : lds(kS + kOpenOff + 4), ps, bar_full + 8 * ps);
      }
      if (wg == 0 && it + 1 == n_tiles && ln == 0) {
        if (warp == kRefill) {
          const int4 c = lds4(kS + kClaimOff);
          uint32_t k;
          asm volatile("atom.global.inc.u32 %0, [%1], %2;\n" : "=r"(k) : "l"((uint64_t)(uint32_t)c.x | ((uint64_t)(uint32_t)c.y << 32)), "r"(c.z) : "memory");
          if (k == 0) sts(kS + kOpenOff, c.w);
        }
        if (warp == 1 && atomicInc(&g_seen, grid + 1) == grid + 1) g_epoch = (unsigned)lds(kS + kOpenOff + 8) / 2;
      }
      wg_wait<1>();
      fence_acc(acc1);
      store_t<true>(acc1, t_addr + kOOff);
      wg_fence();
      proj(acc1, wK, dE);
      wg_commit();
      if (!FAST && it == 0 && warp == kElect && ln == 0) load_r(row_of(1 + wg), 1 + wg, bar_full + 8 * (1 + wg));
      wg_wait<1>();
      fence_acc(acc2);
      store_q_t(acc2, t_addr, t_addr + (ln & 16) * 64, q12_addr, ln & 29);
      wg_fence();
      if (FAST) proj_v(acc2, wV, dE); else proj<true>(acc2, wV, dE);
      wg_commit();
      bar_arrive(4 - wg, 256);
      if (change && warp == kElect && ln == 0) {
        mbar_expect_tx(bar_peek, 16);
        asm volatile("cp.async.bulk.shared::cluster.global.mbarrier::complete_tx::bytes [%0], [%1], 16, [%2];\n" ::"r"(kS + kPeekOff + 16 * wg), "l"(g_state), "r"(bar_peek) : "memory");
      }
      wg_wait<1>();
      fence_acc(acc1);
      store_t<false>(acc1, t_addr + kKOff);
      if (FAST) {
        wg_wait<0>();
        fence_acc(acc2);
        cvt_v();
#pragma unroll
        for (int i = 0; i < 26; i++) asm volatile("" : "+r"(vf[i]));
        sched_barrier();
      }
      publish(wg);
      wg_fence();
      issue_s(acc1, dQ + 512, dK);
      wg_commit();
      if (!FAST) {
        wg_wait<1>();
        fence_acc(acc2);
        cvt_v();
        wg_fence();
      }
      issue_s(acc2, dQ, dK);
      wg_commit();
      if (warp == kElect && ln == 0 && (FAST || it > 0)) tma_out(wg, !FAST && it == 1 ? ((cta & ~1) | wg) * kF : row_of(it - 1));
      wg_wait<1>();
      fence_acc(acc1);
      const float zf = __int_as_float(zero);
      auto q3_dep = [&](const Q3& q, float later) { return ((fmaf(later, zf, q.t) + q.s1) + q.s2) + q.s3; };
      float x[4];
      {
        const bool b0 = ln & 4, b1 = ln & 8, b2 = ln & 16;
#pragma unroll
        for (int h = 0; h < 2; h++) {
          const float* v = acc1 + 2 + h;
          const float x01 = b0 ? v[4] : v[0], x23 = b0 ? v[12] : v[8], x45 = b0 ? v[20] : v[16], x67 = b0 ? v[28] : v[24];
          const float x03 = b1 ? x23 : x01, x47 = b1 ? x67 : x45;
          x[h] = b2 ? x47 : x03;
          const float y01 = b0 ? v[36] : v[32], y23 = b0 ? v[44] : v[40];
          const float y03 = b1 ? y23 : y01;
          x[2 + h] = b2 ? v[48] : y03;
        }
#pragma unroll
        for (int h = 0; h < 4; h++) x[h] = ex2(x[h]);
      }
      float sd = x[0] + x[1];
      if (ln < 18) sd += x[2] + x[3];
      Q3 qd = q3_start(sd, 1);
      float sc;
#pragma unroll
      for (int j = 0; j < 7; j++) set_exp<0>(acc1, j, sc, tail_inv());
      qd = q3_start(q3_dep(qd, sc), 4);
#pragma unroll
      for (int j = 7; j < 12; j++) set_exp<0>(acc1, j, sc, tail_inv());
      sd = q3_dep(qd, sc);
      set_exp<0>(acc1, 12, sc, tail_inv());
      const Q3 qc = q3_start(sc, 1);
      const float sd2 = __shfl_xor_sync(0xffffffffu, sd, 16);
      sched_barrier();
      wg_wait<0>();
      fence_acc(acc2);
      if (change) {
        const int head = wg ^ (cta & 1);
        const unsigned tag = lds(kS + kOpenOff + 8);
        mbar_wait(bar_peek, 0);
        unsigned s0 = lds(kS + kPeekOff + 16 * wg) - tag, s1 = lds(kS + kPeekOff + 16 * wg + 4) - tag;
        if ((s0 | s1) > 1) {
          for (int n = 0; (s0 | s1) > 1 && n < 4096; n++) {
            asm volatile("ld.relaxed.gpu.global.v2.u32 {%0,%1}, [%2];\n" : "=r"(s0), "=r"(s1) : "l"(g_state) : "memory");
            s0 -= tag; s1 -= tag;
          }
          asm volatile("{.reg .pred p, q;\nsetp.le.u32 q, %1, 1;\nbar.red.and.pred p, %2, 128, q;\nselp.b32 %0, %0, 0, p;}\n" : "+r"(s0) : "r"(s0 | s1), "n"(1 + wg) : "memory");
        }
        fast = __any_sync(0xffffffffu, s0 & s1);
        if (fast) {
          const uint4* src = &g_w[head][0][warp * 32 + ln];
#pragma unroll
          for (int i = 0; i < 13; i++) {
            uint32_t* w = i < 5 ? wQ + 12 + 4 * i : wK + 4 * (i - 5);
            asm volatile("ld.relaxed.gpu.global.v4.u32 {%0,%1,%2,%3}, [%4];\n" : "=r"(w[0]), "=r"(w[1]), "=r"(w[2]), "=r"(w[3]) : "l"(src + i * 128) : "memory");
          }
        }
      }
      float sa, sb;
#pragma unroll
      for (int j = 0; j < kLag; j++) set_exp<0>(acc2, j, sa, tail_inv());
      sc = q3_dep(qc, sa);
      bool bad = out_of_range<FAST>(sc);
      const float ic = rcp(sc);
      {
        sd = fmaf(sa, zf, sd) + sd2;
        bad |= out_of_range<FAST>(sd);
        const float id = rcp(sd);
        stsm_x2(wgb + kPOff + 12 * kPGrp + warp * 16 + ln * kPL, pack_bf16(x[0] * id, x[1] * id), pack_bf16(x[2] * id, x[3] * id));
      }
#pragma unroll
      for (int c = 0; c < 4; c++) norm_set<0>(acc1, c, ic, p8_addr() + 2 * kPGrp);
#pragma unroll
      for (int j = kLag; j < 13; j++) set_exp<0>(acc2, j, sa, tail_inv());
      const Q3 qa = q3_start(sa, 1);
      sched_barrier();
#pragma unroll
      for (int j = 0; j < kLag; j++) set_exp<2>(acc2, j, sb, tail_inv());
      sa = q3_dep(qa, sb);
      bad |= out_of_range<FAST>(sa);
      const float ia = rcp(sa);
#pragma unroll
      for (int c = 0; c < 4; c++) norm_set<0>(acc2, c, ia, p8_addr());
#pragma unroll
      for (int j = kLag; j < kRJ; j++) set_exp<2>(acc2, j, sb, tail_inv());
      PIN(sb);
      sched_barrier();
      if (!FAST && it == 0) mbar_wait(bar_w + 8 * (4 * wg + 3), 0);
      asm volatile("cp.async.bulk.wait_group.read 0;\n" ::: "memory");
      if (wg == 1 || it < n_tiles) bar_sync(3 + wg, 256);
      wg_fence();
      proj_r<FAST, true>(acc1, wV, dE, dW);
      wg_commit();
      sched_barrier();
#pragma unroll
      for (int j = kRJ; j < 13; j++) set_exp<2>(acc2, j, sb, tail_inv());
      sb = q3_end(q3_start(sb, 1));
      bad |= out_of_range<FAST>(sb);
      const float ib = rcp(sb);
#pragma unroll
      for (int c = 0; c < 4; c++) norm_set<2>(acc2, c, ib, p8_addr() + kPGrp);
      asm volatile("{.reg .pred p;\nsetp.ne.u32 p, %1, 0;\n@p st.shared.u8 [%0], %1;}\n" ::"r"(kS + kBadOff + 32 * wg + min(it, 31)), "r"((uint32_t)bad) : "memory");
      wg_wait<0>();
      fence_acc(acc1);
      publish(wg);
      asm volatile("xor.b32 %0, %0, %1;\n" : "+r"(ln) : "r"(zero));
    };
    auto loops = [&](auto wgc) __attribute__((always_inline)) {
      auto won = [&]() { return it + 1 < lds(kS + kOpenOff); };
      do iter(wgc, IC<0>()); while (!fast && (it + 1 < n_tiles || (wgc == 0 && won())));
      if (fast) {
#pragma unroll
        for (int i = 0; i < 12; i++) wQ[i] = wV[i];
#pragma unroll
        for (int i = 12; i < 32; i++) asm("sub.rn.bf16x2 %0, %0, %1;\n" : "+r"(wV[i]) : "r"(wQ[i]));
#pragma unroll
        for (int s = 0; s < 3; s++) ldsm_x4_t(t_addr + kWsOff + s * 2048, wV[4 * s], wV[4 * s + 1], wV[4 * s + 2], wV[4 * s + 3]);
        do iter(wgc, IC<1>()); while (it + 1 < n_tiles || (wgc == 0 && won()));
      }
    };

    auto load_frags = [&](uint32_t (&w)[32], int m) {
      mbar_wait(bar_w + 8 * (4 * wg_r + m), 0);
      const uint32_t a = m < 2 ? t_addr + m * 16384 : t_addr - (kWGBase - kEStage) - (tid >> 7) * (kWGRegion - kEStage);
#pragma unroll
      for (int s = 0; s < 8; s++) ldsm_x4_t(a + s * 2048, w[4 * s], w[4 * s + 1], w[4 * s + 2], w[4 * s + 3]);
    };
    load_frags(wQ, 0);
    scale_wq(wQ);
    load_frags(wK, 1);
    load_frags(wV, 2);
    bar_sync(1 + wg_r, 128);
    if (warp < 2) st_zero(kS + (2 + 2 * wg_r + warp) * kEHalf + kF * 128 + lane * 16);
    if (tid >= 156) {
      const uint8_t* p = p_e + (size_t)(3 * grid + cta) * (kF * kD * 2) + (tid - 156) * 256;
      asm volatile("prefetch.global.L2 [%0];\nprefetch.global.L2 [%0 + 128];\n" ::"l"(p));
    }
    if (wg_r == 1) bar_sync(4, 256);
#pragma unroll
    for (int i = 0; i < 52; i++) asm volatile("" : "=f"(acc1[i]));
#pragma unroll
    for (int i = 0; i < 26; i++) asm volatile("" : "=r"(vf[i]));
    if (wg_r == 1) loops(IC<1>()); else loops(IC<0>());

    int tid2;
    asm volatile("mov.u32 %0, %tid.x;\n" : "=r"(tid2));
    const int wg = __shfl_sync(0xffffffffu, tid2 >> 7, 0);
    wg_fence();
    issue_pv(acc1, vf, desc_p(kS + kWGBase + wg * kWGRegion + kPOff), z0, z1);
    wg_commit();
    if (wg == 0 && it < n_tiles) bar_arrive(4, 256);
    wg_wait<0>();
    fence_acc(acc1);
    store_t<true>(acc1, t_addr + kOOff);
    publish(wg);
    if (warp == kElect && ln == 0) tma_out(wg, it == n_tiles ? lds(kS + kOpenOff + 4) : row_of(it));
    if (tid2 == 64) mbar_wait(bar_full + 8 * (n_tiles & 3), (n_tiles >> 2) & 1);
    __syncthreads();
    if (!__any_sync(0xffffffffu, lds16(kS + kBadOff + 2 * ln))) {
      asm volatile("cp.async.bulk.wait_group.read 0;\n" ::: "memory");
      return;
    }
  }
  exact_redo(&tm_e, &tm_o, &tm_q, &tm_k, &tm_v, n_tiles);
}

typedef CUresult (*EncodeFn)(CUtensorMap*, CUtensorMapDataType, cuuint32_t, void*, const cuuint64_t*, const cuuint64_t*,
                             const cuuint32_t*, const cuuint32_t*, CUtensorMapInterleave, CUtensorMapSwizzle,
                             CUtensorMapL2promotion, CUtensorMapFloatOOBfill);

}

extern "C" void kernel_launch(void* const* d_in, const int* in_sizes, int n_in, void* d_out, int out_size) {
  static EncodeFn encode = nullptr;
  static int num_sms = 0;
  if (!encode) {
    void* fn = nullptr;
    cudaDriverEntryPointQueryResult qres;
    cudaGetDriverEntryPoint("cuTensorMapEncodeTiled", &fn, cudaEnableDefault, &qres);
    encode = (EncodeFn)fn;
    int dev = 0;
    cudaGetDevice(&dev);
    cudaDeviceGetAttribute(&num_sms, cudaDevAttrMultiProcessorCount, dev);
    cudaFuncSetAttribute(autoint_kernel, cudaFuncAttributeMaxDynamicSharedMemorySize, kSmemBytes);
  }
  auto make = [&](void* p, uint64_t cols, uint64_t rows, uint32_t box_rows, CUtensorMapL2promotion promo) {
    CUtensorMap tm;
    cuuint64_t dims[2] = {cols, rows};
    cuuint64_t strides[1] = {cols * 2};
    cuuint32_t box[2] = {64, box_rows};
    cuuint32_t estr[2] = {1, 1};
    encode(&tm, CU_TENSOR_MAP_DATA_TYPE_BFLOAT16, 2, p, dims, strides, box, estr, CU_TENSOR_MAP_INTERLEAVE_NONE,
           CU_TENSOR_MAP_SWIZZLE_128B, promo, CU_TENSOR_MAP_FLOAT_OOB_FILL_NONE);
    return tm;
  };
  const CUtensorMap tm_e = make(d_in[0], kD, (uint64_t)kB * kF, kF, CU_TENSOR_MAP_L2_PROMOTION_L2_128B);
  const CUtensorMap tm_o = make(d_out, kD, (uint64_t)kB * kF, kF, CU_TENSOR_MAP_L2_PROMOTION_NONE);
  const CUtensorMap tm_q = make(d_in[1], 64, 256, 128, CU_TENSOR_MAP_L2_PROMOTION_L2_256B);
  const CUtensorMap tm_k = make(d_in[2], 64, 256, 128, CU_TENSOR_MAP_L2_PROMOTION_L2_256B);
  const CUtensorMap tm_v = make(d_in[3], 64, 256, 128, CU_TENSOR_MAP_L2_PROMOTION_L2_256B);
  const CUtensorMap tm_r = make(d_in[4], 128, 128, 128, CU_TENSOR_MAP_L2_PROMOTION_L2_256B);
  const int grid = (num_sms < 2 ? 2 : num_sms < kB / 8 ? num_sms : kB / 8) & ~1;
  const int n_base = kB / grid, rem = kB - n_base * grid, split = 2 * (rem + 2 * kSkip) <= grid;
  autoint_kernel<<<grid + 2, 256, kSmemBytes>>>(tm_e, tm_o, tm_q, tm_k, tm_v, tm_r, (const uint8_t*)d_in[0],
                                             WPtrs{{(const uint8_t*)d_in[1], (const uint8_t*)d_in[2], (const uint8_t*)d_in[3], (const uint8_t*)d_in[4]}},
                                             grid, n_base, split ? 0 : rem, split ? kSkip : 0, 0, split ? rem + 2 * kSkip : 0);
}
```
